```python
import torch

def _softmax(x, axis=-1):
    return torch.softmax(x, dim=axis)
def _gelu(x):
    return torch.nn.functional.gelu(x, approximate="tanh")
def _silu(x):
    return torch.nn.functional.silu(x)
def _sigmoid(x):
    return torch.sigmoid(x)
def _layernorm(x, axis=-1, eps=1e-5):
    m = x.mean(dim=axis, keepdim=True)
    v = x.var(dim=axis, keepdim=True, unbiased=False)
    return (x - m) / torch.sqrt(v + eps)
def _scatter_add(tgt, idx, src, axis=0):
    return tgt.clone().index_add_(axis, idx, src)
def _segment_sum(src, seg, n):
    out = torch.zeros((n,) + src.shape[1:], dtype=src.dtype)
    return out.index_add_(0, seg, src)
def _pad(x, pw):
    flat = tuple(v for pair in reversed(pw) for v in pair)
    return torch.nn.functional.pad(x, flat)

kernel_name = 'sequential_preLN__mha_block_cached__dense_activation_squared_relu__decode'

def setup_inputs():

    _w = (lambda a: (lambda t: t.to(torch.bfloat16) if t.is_floating_point() else t)(torch.as_tensor(a)))
    def _A_setup():
        B, Sq, D = 8, 1, 448
        H, Sk, Dh = 16, 4096, 256
        return {
            "x": _w((lambda *s: torch.randn(*s, dtype=torch.bfloat16) * 0.05)(B, Sq, D)),
            "k_cache": _w((lambda *s: torch.randn(*s, dtype=torch.bfloat16) * 3.2)(B, H, Sk, Dh)),
            "v_cache": _w((lambda *s: torch.randn(*s, dtype=torch.bfloat16) * 0.4)(B, H, Sk, Dh)),
            "wq": _w((lambda *s: torch.randn(*s, dtype=torch.bfloat16) * 3.2)(D, H * Dh) * (D ** -0.5)),
            "wo": _w((lambda *s: torch.randn(*s, dtype=torch.bfloat16) * 0.4)(H * Dh, D) * ((H * Dh) ** -0.5)),
        }
    _A_in = _A_setup()

    def _B_setup():
        B, S, D, F = 8, 1, 448, 1792
        return {
            "x": _w((lambda *s: torch.randn(*s, dtype=torch.bfloat16) * 0.05)(B, S, D)),
            "w1": _w((lambda *s: torch.randn(*s, dtype=torch.bfloat16) * 0.05)(D, F)),
            "b1": _w((lambda *s: torch.randn(*s, dtype=torch.bfloat16) * 0.8)(F)),
            "w2": _w((lambda *s: torch.randn(*s, dtype=torch.bfloat16) * 0.05)(F, D)),
            "b2": _w((lambda *s: torch.randn(*s, dtype=torch.bfloat16) * 3.2)(D)),
        }
    _B_in = _B_setup()

    return {
        "A_x": _A_in["x"],
        "A_k_cache": _A_in["k_cache"],
        "A_v_cache": _A_in["v_cache"],
        "A_wq": _A_in["wq"],
        "A_wo": _A_in["wo"],
        "B_x": _B_in["x"],
        "B_w1": _B_in["w1"],
        "B_b1": _B_in["b1"],
        "B_w2": _B_in["w2"],
        "B_b2": _B_in["b2"],
    }

def reference(A_x, A_k_cache, A_v_cache, A_wq, A_wo, B_x, B_w1, B_b1, B_w2, B_b2):
    def _A_ref(x, k_cache, v_cache, wq, wo):
        B, Sq, D = x.shape
        H, Dh = 16, 256
        q = (lambda x, *d: x.permute(*d))((x @ wq).reshape(B, Sq, H, Dh), 0, 2, 1, 3)
        scores = torch.einsum("bhqd,bhkd->bhqk", q, k_cache) * (Dh ** -0.5)
        p = _softmax(scores, axis=-1)
        o = torch.einsum("bhqk,bhkd->bhqd", p, v_cache)
        return (lambda x, *d: x.permute(*d))(o, 0, 2, 1, 3).reshape(B, Sq, H * Dh) @ wo

    def _B_ref(x, w1, b1, w2, b2):
        h = torch.einsum("bsd,df->bsf", x, w1) + b1
        zero = torch.zeros_like(h)
        r = torch.where(h > zero, h, zero)
        h = r * r
        out = torch.einsum("bsf,fd->bsd", h, w2) + b2
        return out

    x = A_x
    h = x + _A_ref(_layernorm(x, axis=-1), A_k_cache, A_v_cache, A_wq, A_wo)
    h2 = h + _B_ref(_layernorm(h, axis=-1), B_w1, B_b1, B_w2, B_b2)
    return h2
```

```cpp
#include <cuda_runtime.h>
#include <cuda_bf16.h>
#include <cuda.h>
#include <stdint.h>

namespace {

constexpr int NB = 8, DM = 448, NH = 16, SK = 4096, DH = 256, FF = 1792;
constexpr int NCTA = NB * NH;
constexpr int NTAIL = 112;
constexpr int TILE_KEYS = 64;
constexpr int STAGE = TILE_KEYS * DH * 2;
constexpr int NS = 6;
constexpr int KT = SK / TILE_KEYS;
constexpr int NT = 2 * KT;
constexpr int KPW = TILE_KEYS / 8;
constexpr int NTHREADS = 288;
constexpr int XP = 456;
constexpr int SPIN_MAX = 1 << 22;

constexpr int OFF_RING = 0;
constexpr int OFF_A = OFF_RING + NS * STAGE;
constexpr int OFF_B = OFF_A + 17408;
constexpr int OFF_C = OFF_B + 9216;
constexpr int OFF_M = OFF_C + NB * XP * 2;
constexpr int OFF_BAR = OFF_M + 256;
constexpr int SMEM_BYTES = OFF_BAR + 2 * NS * 8 + 1024;

__device__ uint32_t g_epoch;
__device__ __align__(128) uint32_t g_q[2][NB * NH * DH / 2];
__device__ __align__(128) uint32_t g_o[2][NH * NB * DH / 2];
__device__ __align__(128) uint32_t g_h[2][NB * DM / 2];
__device__ __align__(128) uint32_t g_g[2][2 * NTAIL * 32];
__device__ __align__(128) uint32_t g_p2[7 * 16 * 16 * 32];

#define PROF(cond, i)

__device__ __forceinline__ uint32_t smem_u32(const void* p) { return (uint32_t)__cvta_generic_to_shared(p); }

__device__ __forceinline__ void mbar_init(uint32_t a, uint32_t c) {
    asm volatile("mbarrier.init.shared.b64 [%0], %1;" :: "r"(a), "r"(c) : "memory");
}
__device__ __forceinline__ void mbar_expect_tx(uint32_t a, uint32_t bytes) {
    asm volatile("mbarrier.arrive.expect_tx.shared.b64 _, [%0], %1;" :: "r"(a), "r"(bytes) : "memory");
}
__device__ __forceinline__ void mbar_arrive(uint32_t a) {
    asm volatile("mbarrier.arrive.shared.b64 _, [%0];" :: "r"(a) : "memory");
}
__device__ __forceinline__ void mbar_wait(uint32_t a, uint32_t parity) {
    uint32_t ok;
    int it = 0;
    do {
        asm volatile("{\n.reg .pred p;\nmbarrier.try_wait.parity.shared.b64 p, [%1], %2;\nselp.u32 %0, 1, 0, p;\n}"
                     : "=r"(ok) : "r"(a), "r"(parity) : "memory");
    } while (!ok && ++it < SPIN_MAX);
}
__device__ __forceinline__ void bulk_load(uint32_t dst, const void* src, uint32_t bytes, uint32_t bar, uint64_t pol) {
    asm volatile("cp.async.bulk.shared::cluster.global.mbarrier::complete_tx::bytes.L2::cache_hint [%0], [%1], %2, [%3], %4;"
                 :: "r"(dst), "l"(src), "r"(bytes), "r"(bar), "l"(pol) : "memory");
}
__device__ __forceinline__ void tma_2d(uint32_t dst, const CUtensorMap* tm, int c0, int c1, uint32_t bar) {
    asm volatile("cp.async.bulk.tensor.2d.shared::cluster.global.mbarrier::complete_tx::bytes [%0], [%1, {%3, %4}], [%2];"
                 :: "r"(dst), "l"(tm), "r"(bar), "r"(c0), "r"(c1) : "memory");
}
__device__ __forceinline__ void cbar() { asm volatile("bar.sync 1, 256;" ::: "memory"); }

__device__ __forceinline__ uint4 lds128(uint32_t a) {
    uint4 v;
    asm volatile("ld.shared.v4.u32 {%0,%1,%2,%3}, [%4];" : "=r"(v.x), "=r"(v.y), "=r"(v.z), "=r"(v.w) : "r"(a) : "memory");
    return v;
}
__device__ __forceinline__ uint4 ldm4(uint32_t a) {
    uint4 v;
    asm volatile("ldmatrix.sync.aligned.m8n8.x4.shared.b16 {%0,%1,%2,%3}, [%4];"
                 : "=r"(v.x), "=r"(v.y), "=r"(v.z), "=r"(v.w) : "r"(a) : "memory");
    return v;
}
__device__ __forceinline__ uint4 ldm4t(uint32_t a) {
    uint4 v;
    asm volatile("ldmatrix.sync.aligned.m8n8.x4.trans.shared.b16 {%0,%1,%2,%3}, [%4];"
                 : "=r"(v.x), "=r"(v.y), "=r"(v.z), "=r"(v.w) : "r"(a) : "memory");
    return v;
}
__device__ __forceinline__ void mma16816(float (&c)[4], uint32_t a0, uint32_t a1, uint32_t a2, uint32_t a3, uint32_t b0, uint32_t b1) {
    asm volatile("mma.sync.aligned.m16n8k16.row.col.f32.bf16.bf16.f32 {%0,%1,%2,%3}, {%4,%5,%6,%7}, {%8,%9}, {%0,%1,%2,%3};"
                 : "+f"(c[0]), "+f"(c[1]), "+f"(c[2]), "+f"(c[3])
                 : "r"(a0), "r"(a1), "r"(a2), "r"(a3), "r"(b0), "r"(b1));
}
__device__ __forceinline__ uint4 ld_rlx128(const uint32_t* p) {
    uint4 v;
    asm volatile("ld.relaxed.gpu.global.v4.u32 {%0,%1,%2,%3}, [%4];" : "=r"(v.x), "=r"(v.y), "=r"(v.z), "=r"(v.w) : "l"(p) : "memory");
    return v;
}
__device__ __forceinline__ uint2 ld_rlx64(const uint32_t* p) {
    uint2 v;
    asm volatile("ld.relaxed.gpu.global.v2.u32 {%0,%1}, [%2];" : "=r"(v.x), "=r"(v.y) : "l"(p) : "memory");
    return v;
}
__device__ __forceinline__ uint32_t ldg32_now(const void* p) {
    uint32_t v;
    asm volatile("ld.global.nc.u32 %0, [%1];" : "=r"(v) : "l"(p) : "memory");
    return v;
}
__device__ __forceinline__ void st_rlx32(uint32_t* p, uint32_t v) {
    asm volatile("st.relaxed.gpu.global.u32 [%0], %1;" :: "l"(p), "r"(v) : "memory");
}
__device__ __forceinline__ void st_rlx64(uint32_t* p, uint32_t a, uint32_t b) {
    asm volatile("st.relaxed.gpu.global.v2.u32 [%0], {%1,%2};" :: "l"(p), "r"(a), "r"(b) : "memory");
}

__device__ __forceinline__ float bf_lo(uint32_t w) { return __uint_as_float(w << 16); }
__device__ __forceinline__ float bf_hi(uint32_t w) { return __uint_as_float(w & 0xffff0000u); }
__device__ __forceinline__ float rbf(float x) { return __bfloat162float(__float2bfloat16_rn(x)); }
__device__ __forceinline__ uint32_t pack_bf(float lo, float hi) {
    __nv_bfloat162 v = __floats2bfloat162_rn(lo, hi);
    return *reinterpret_cast<uint32_t*>(&v);
}
__device__ __forceinline__ uint32_t enc(uint32_t w) { return w == 0xffffffffu ? 0x80008000u : ~w; }
__device__ __forceinline__ bool valid4(const uint4& v) { return v.x != 0 && v.y != 0 && v.z != 0 && v.w != 0; }
__device__ __forceinline__ uint4 dec4(const uint4& v) { return make_uint4(~v.x, ~v.y, ~v.z, ~v.w); }

__device__ __forceinline__ float warp_sum(float v) {
#pragma unroll
    for (int o = 16; o > 0; o >>= 1) v += __shfl_xor_sync(0xffffffffu, v, o);
    return v;
}

__device__ __forceinline__ void layernorm_row(const uint4& r0, const uint4& r1, int lane, uint32_t dst_row) {
    const bool act = lane < 28;
    float v[16];
    const uint32_t w[8] = {r0.x, r0.y, r0.z, r0.w, r1.x, r1.y, r1.z, r1.w};
#pragma unroll
    for (int i = 0; i < 8; i++) { v[2 * i] = act ? bf_lo(w[i]) : 0.f; v[2 * i + 1] = act ? bf_hi(w[i]) : 0.f; }
    float s = 0.f;
#pragma unroll
    for (int i = 0; i < 16; i++) s += v[i];
    const float mean = warp_sum(s) * (1.0f / DM);
    float q = 0.f;
#pragma unroll
    for (int i = 0; i < 16; i++) { const float d = v[i] - mean; q = fmaf(d, d, q); }
    const float var = warp_sum(act ? q : 0.f) * (1.0f / DM);
    const float mb = rbf(mean);
    const float sd = rbf(sqrtf(rbf(rbf(var) + 1e-5f)));
    uint32_t o[8];
#pragma unroll
    for (int i = 0; i < 8; i++) o[i] = pack_bf(rbf(v[2 * i] - mb) / sd, rbf(v[2 * i + 1] - mb) / sd);
    if (act) {
        asm volatile("st.shared.v4.u32 [%0], {%1,%2,%3,%4};" :: "r"(dst_row + lane * 16), "r"(o[0]), "r"(o[1]), "r"(o[2]), "r"(o[3]) : "memory");
        asm volatile("st.shared.v4.u32 [%0], {%1,%2,%3,%4};" :: "r"(dst_row + 448 + lane * 16), "r"(o[4]), "r"(o[5]), "r"(o[6]), "r"(o[7]) : "memory");
    }
}

__global__ void __launch_bounds__(NTHREADS, 1)
fused_decode_kernel(const __nv_bfloat16* __restrict__ x, const __nv_bfloat16* __restrict__ kc,
                    const __nv_bfloat16* __restrict__ vc, const __nv_bfloat16* __restrict__ wq,
                    const __nv_bfloat16* __restrict__ b1, const __nv_bfloat16* __restrict__ b2,
                    __nv_bfloat16* __restrict__ out,
                    const __grid_constant__ CUtensorMap tm_wo, const __grid_constant__ CUtensorMap tm_w1,
                    const __grid_constant__ CUtensorMap tm_w2) {
    extern __shared__ uint8_t smem_raw[];
    const uint32_t sraw = smem_u32(smem_raw);
    const uint32_t sb = (sraw + 1023u) & ~1023u;
    uint8_t* const sp = smem_raw + (sb - sraw);

    const int tid = threadIdx.x, warp = tid >> 5, lane = tid & 31;
    const int cta = blockIdx.x;
    const int hd = cta >> 3, bj = cta & 7;
    const bool tail = bj < 7;
    const int r = hd * 7 + bj;
    const uint32_t bar_full = sb + OFF_BAR, bar_empty = bar_full + NS * 8;

    if (warp == 8) {
        const char* kp = reinterpret_cast<const char*>(kc) + (size_t)(bj * NH + hd) * SK * DH * 2;
        const char* vp = reinterpret_cast<const char*>(vc) + (size_t)(bj * NH + hd) * SK * DH * 2;
        uint64_t pol;
        asm volatile("createpolicy.fractional.L2::evict_first.b64 %0, 1.0;" : "=l"(pol));
        if (lane == 0) {
            PROF(true, 0);
#pragma unroll
            for (int s = 0; s < NS; s++) { mbar_init(bar_full + s * 8, 1); mbar_init(bar_empty + s * 8, 8); }
            asm volatile("fence.mbarrier_init.release.cluster;" ::: "memory");
#pragma unroll
            for (int s = 0; s < NS - 1; s++) {
                mbar_expect_tx(bar_full + s * 8, STAGE);
                bulk_load(sb + OFF_RING + s * STAGE, kp + (size_t)s * STAGE, STAGE, bar_full + s * 8, pol);
            }
        }
        uint32_t epoch;
        asm volatile("ld.relaxed.gpu.global.u32 %0, [%1];" : "=r"(epoch) : "l"(&g_epoch) : "memory");
        epoch += 1;
        __syncthreads();
        if (lane == 0) {
            int s = NS - 1, u = 0;
            for (int t = NS - 1; t < NT + (tail ? 3 : 0); t++) {
                mbar_wait(bar_empty + s * 8, (s == NS - 1 ? u : u - 1) & 1);
                const uint32_t dst = sb + OFF_RING + s * STAGE, fb = bar_full + s * 8;
                if (t < NT) {
                    mbar_expect_tx(fb, STAGE);
                    bulk_load(dst, t < KT ? kp + (size_t)t * STAGE : vp + (size_t)(t - KT) * STAGE, STAGE, fb, pol);
                    if (t == NT - 8) {
                        asm volatile("prefetch.tensormap [%0];" :: "l"(&tm_wo) : "memory");
                        asm volatile("prefetch.tensormap [%0];" :: "l"(&tm_w1) : "memory");
                        asm volatile("prefetch.tensormap [%0];" :: "l"(&tm_w2) : "memory");
                    }
                } else if (t == NT) {
                    mbar_expect_tx(fb, DH * 128);
                    tma_2d(dst, &tm_wo, bj * 64, hd * DH, fb);
                } else if (t == NT + 1) {
                    mbar_expect_tx(fb, DM * 32);
                    tma_2d(dst, &tm_w1, r * 16, 0, fb);
                    tma_2d(dst + 224 * 32, &tm_w1, r * 16, 224, fb);
                } else {
                    mbar_expect_tx(fb, FF * 16);
#pragma unroll
                    for (int i = 0; i < 7; i++) tma_2d(dst + i * 4096, &tm_w2, (r >> 1) * 8, i * 256, fb);
                }
                if (++s == NS) { s = 0; u++; }
            }
        }
        __syncwarp();
        if (!tail) return;
        const int rb = hd >> 1, col = bj * 64 + (hd & 1) * 32 + (lane & 7) * 4;
        const uint2 xr = make_uint2(ldg32_now(x + rb * DM + col), ldg32_now(x + rb * DM + col + 2));
        const uint32_t* src = g_p2 + ((bj * 16 + hd) * 16 + (lane >> 3)) * 32 + (lane & 7) * 4;
        const uint32_t tag = epoch & 1;
        uint4 v[4];
        uint32_t pend = 15;
        for (int it = 0; pend && it < SPIN_MAX; it++) {
#pragma unroll
            for (int i = 0; i < 4; i++) if (pend >> i & 1) v[i] = ld_rlx128(src + i * 128);
#pragma unroll
            for (int i = 0; i < 4; i++)
                if ((((v[i].x ^ tag) | (v[i].y ^ tag) | (v[i].z ^ tag) | (v[i].w ^ tag)) & 1) == 0) pend &= ~(1u << i);
        }
        __syncwarp();
        PROF(lane == 0, 8);
        float a0 = (__uint_as_float(v[0].x) + __uint_as_float(v[1].x)) + (__uint_as_float(v[2].x) + __uint_as_float(v[3].x));
        float a1 = (__uint_as_float(v[0].y) + __uint_as_float(v[1].y)) + (__uint_as_float(v[2].y) + __uint_as_float(v[3].y));
        float a2 = (__uint_as_float(v[0].z) + __uint_as_float(v[1].z)) + (__uint_as_float(v[2].z) + __uint_as_float(v[3].z));
        float a3 = (__uint_as_float(v[0].w) + __uint_as_float(v[1].w)) + (__uint_as_float(v[2].w) + __uint_as_float(v[3].w));
#pragma unroll
        for (int o = 8; o <= 16; o <<= 1) {
            a0 += __shfl_xor_sync(0xffffffffu, a0, o);
            a1 += __shfl_xor_sync(0xffffffffu, a1, o);
            a2 += __shfl_xor_sync(0xffffffffu, a2, o);
            a3 += __shfl_xor_sync(0xffffffffu, a3, o);
        }
        if (lane < 8) {
            const uint32_t h0 = pack_bf(bf_lo(xr.x) + rbf(a0), bf_hi(xr.x) + rbf(a1));
            const uint32_t h1 = pack_bf(bf_lo(xr.y) + rbf(a2), bf_hi(xr.y) + rbf(a3));
            st_rlx64(&g_h[tag][(rb * DM + col) >> 1], enc(h0), enc(h1));
        }
        return;
    }

    const int g = lane >> 2, t4 = lane & 3;
    const uint32_t s_wq = sb + OFF_RING + (NS - 1) * STAGE;
#pragma unroll
    for (int i = 0; i < 7; i++) {
        const int idx = tid + i * 256, row = idx >> 2, ch = idx & 3;
        asm volatile("cp.async.cg.shared.global.L2::128B [%0], [%1], 16;"
                     :: "r"(s_wq + row * 64 + ((ch ^ ((row >> 1) & 3)) << 4)),
                        "l"(wq + (size_t)row * (NH * DH) + cta * 32 + ch * 8) : "memory");
    }
    asm volatile("cp.async.commit_group;" ::: "memory");
    uint4 xr0 = make_uint4(0, 0, 0, 0), xr1 = xr0;
    if (lane < 28) {
        xr0 = *reinterpret_cast<const uint4*>(x + warp * DM + lane * 8);
        xr1 = *reinterpret_cast<const uint4*>(x + warp * DM + 224 + lane * 8);
    }
    uint32_t epoch;
    asm volatile("ld.relaxed.gpu.global.u32 %0, [%1];" : "=r"(epoch) : "l"(&g_epoch) : "memory");
    epoch += 1;
    const uint32_t par = epoch & 1;
    __syncthreads();

    layernorm_row(xr0, xr1, lane, sb + OFF_C + warp * (XP * 2));
    asm volatile("cp.async.wait_group 0;" ::: "memory");
    cbar();

    float* red_b = reinterpret_cast<float*>(sp + OFF_B);
    if (warp < 7) {
        float acc[4][4] = {};
#pragma unroll
        for (int p = 0; p < 2; p++) {
            const uint4 a = ldm4(sb + OFF_C + (lane & 7) * (XP * 2) + (warp * 64 + p * 32 + (lane >> 3) * 8) * 2);
#pragma unroll
            for (int s = 0; s < 2; s++) {
                const int row = warp * 64 + p * 32 + s * 16 + ((lane >> 3) & 1) * 8 + (lane & 7);
#pragma unroll
                for (int np = 0; np < 2; np++) {
                    const int ch = np * 2 + (lane >> 4);
                    const uint4 bw = ldm4t(s_wq + row * 64 + ((ch ^ ((row >> 1) & 3)) << 4));
                    mma16816(acc[np * 2], s ? a.z : a.x, 0, s ? a.w : a.y, 0, bw.x, bw.y);
                    mma16816(acc[np * 2 + 1], s ? a.z : a.x, 0, s ? a.w : a.y, 0, bw.z, bw.w);
                }
            }
        }
#pragma unroll
        for (int n = 0; n < 4; n++)
            *reinterpret_cast<float2*>(red_b + (warp * 8 + g) * 40 + n * 8 + t4 * 2) = make_float2(acc[n][0], acc[n][1]);
    }
    asm volatile("fence.proxy.async.shared::cta;" ::: "memory");
    cbar();
    if (lane == 0) mbar_arrive(bar_empty + (NS - 1) * 8);
    if (tid < 128) {
        const int b = tid >> 4, wd = tid & 15;
        float s0 = 0.f, s1 = 0.f;
#pragma unroll
        for (int w = 0; w < 7; w++) {
            const float2 p = *reinterpret_cast<const float2*>(red_b + (w * 8 + b) * 40 + wd * 2);
            s0 += p.x; s1 += p.y;
        }
        st_rlx32(&g_q[par][b * (NH * DH / 2) + cta * 16 + wd], enc(pack_bf(s0, s1)));
    } else {
        const int i = tid - 128;
        g_q[par ^ 1][(i >> 4) * (NH * DH / 2) + cta * 16 + (i & 15)] = 0;
        g_o[par ^ 1][cta * 128 + i] = 0;
        if (tail && i < 64) g_g[par ^ 1][((i >> 5) * NTAIL + r) * 32 + (i & 31)] = 0;
        if (tail && i < 16) g_h[par ^ 1][(((hd >> 1) * DM + bj * 64 + (hd & 1) * 32) >> 1) + i] = 0;
    }
    PROF(tid == 0, 1);

    float q[32];
    {
        const uint32_t* src = &g_q[par][bj * (NH * DH / 2) + hd * (DH / 2) + (lane & 7) * 4];
        uint4 v[4];
        uint32_t pend = 15;
        for (int it = 0; pend && it < SPIN_MAX; it++) {
#pragma unroll
            for (int i = 0; i < 4; i++) if (pend >> i & 1) v[i] = ld_rlx128(src + i * 32);
#pragma unroll
            for (int i = 0; i < 4; i++) if (valid4(v[i])) pend &= ~(1u << i);
        }
        __syncwarp();
#pragma unroll
        for (int i = 0; i < 4; i++) {
            const uint4 d = dec4(v[i]);
            q[i * 8 + 0] = bf_lo(d.x); q[i * 8 + 1] = bf_hi(d.x);
            q[i * 8 + 2] = bf_lo(d.y); q[i * 8 + 3] = bf_hi(d.y);
            q[i * 8 + 4] = bf_lo(d.z); q[i * 8 + 5] = bf_hi(d.z);
            q[i * 8 + 6] = bf_lo(d.w); q[i * 8 + 7] = bf_hi(d.w);
        }
    }
    PROF(tid == 0, 2);

    float* sc = reinterpret_cast<float*>(sp + OFF_A);
    int st = 0, ph = 0;
    float mx = -INFINITY;
    for (int t = 0; t < KT; t++) {
        mbar_wait(bar_full + st * 8, ph);
        const uint32_t base = sb + OFF_RING + st * STAGE + (warp * KPW + (lane >> 3)) * 512 + (lane & 7) * 16;
        float d[KPW / 4];
#pragma unroll
        for (int i = 0; i < KPW / 4; i++) {
            float a0 = 0.f, a1 = 0.f;
#pragma unroll
            for (int j = 0; j < 4; j++) {
                const uint4 v = lds128(base + i * 2048 + j * 128);
                a0 = fmaf(q[j * 8 + 0], bf_lo(v.x), a0); a1 = fmaf(q[j * 8 + 1], bf_hi(v.x), a1);
                a0 = fmaf(q[j * 8 + 2], bf_lo(v.y), a0); a1 = fmaf(q[j * 8 + 3], bf_hi(v.y), a1);
                a0 = fmaf(q[j * 8 + 4], bf_lo(v.z), a0); a1 = fmaf(q[j * 8 + 5], bf_hi(v.z), a1);
                a0 = fmaf(q[j * 8 + 6], bf_lo(v.w), a0); a1 = fmaf(q[j * 8 + 7], bf_hi(v.w), a1);
            }
            d[i] = a0 + a1;
        }
        __syncwarp();
        if (lane == 0) mbar_arrive(bar_empty + st * 8);
#pragma unroll
        for (int i = 0; i < KPW / 4; i++) {
#pragma unroll
            for (int o = 1; o <= 4; o <<= 1) d[i] += __shfl_xor_sync(0xffffffffu, d[i], o);
            const float s = rbf(d[i]) * 0.0625f;
            mx = fmaxf(mx, s);
            if ((lane & 7) == 0) sc[t * TILE_KEYS + warp * KPW + i * 4 + (lane >> 3)] = s;
        }
        if (++st == NS) { st = 0; ph ^= 1; }
    }
    PROF(tid == 0, 3);

    float* sm_m = reinterpret_cast<float*>(sp + OFF_M);
    mx = fmaxf(mx, __shfl_xor_sync(0xffffffffu, mx, 8));
    mx = fmaxf(mx, __shfl_xor_sync(0xffffffffu, mx, 16));
    if (lane == 0) sm_m[warp] = mx;
    cbar();
#pragma unroll
    for (int w = 0; w < 8; w++) mx = fmaxf(mx, sm_m[w]);
    {
        float e[16], sum = 0.f;
#pragma unroll
        for (int i = 0; i < 4; i++) {
            const float4 s = *reinterpret_cast<const float4*>(sc + i * 1024 + tid * 4);
            e[i * 4 + 0] = expf(s.x - mx); e[i * 4 + 1] = expf(s.y - mx);
            e[i * 4 + 2] = expf(s.z - mx); e[i * 4 + 3] = expf(s.w - mx);
            sum += (e[i * 4] + e[i * 4 + 1]) + (e[i * 4 + 2] + e[i * 4 + 3]);
        }
        sum = warp_sum(sum);
        if (lane == 0) sm_m[8 + warp] = sum;
        cbar();
        sum = 0.f;
#pragma unroll
        for (int w = 0; w < 8; w++) sum += sm_m[8 + w];
        const float inv = 1.0f / sum;
#pragma unroll
        for (int i = 0; i < 4; i++)
            *reinterpret_cast<float4*>(sc + i * 1024 + tid * 4) =
                make_float4(rbf(e[i * 4] * inv), rbf(e[i * 4 + 1] * inv), rbf(e[i * 4 + 2] * inv), rbf(e[i * 4 + 3] * inv));
        cbar();
    }
    PROF(tid == 0, 4);

    uint32_t bias1a = 0, bias1b = 0, bias2w = 0;
    if (warp == 0 && tail) {
        bias1a = ldg32_now(b1 + r * 16 + t4 * 2);
        bias1b = ldg32_now(b1 + r * 16 + 8 + t4 * 2);
        bias2w = ldg32_now(b2 + (r >> 1) * 8 + (lane & 6));
    }

    float o[8] = {};
    for (int t = 0; t < KT; t++) {
        float p[KPW];
#pragma unroll
        for (int i = 0; i < KPW / 4; i++) {
            const float4 pp = *reinterpret_cast<const float4*>(sc + t * TILE_KEYS + warp * KPW + i * 4);
            p[i * 4] = pp.x; p[i * 4 + 1] = pp.y; p[i * 4 + 2] = pp.z; p[i * 4 + 3] = pp.w;
        }
        mbar_wait(bar_full + st * 8, ph);
        const uint32_t base = sb + OFF_RING + st * STAGE + warp * KPW * 512 + lane * 16;
#pragma unroll
        for (int i = 0; i < KPW; i++) {
            const uint4 v = lds128(base + i * 512);
            o[0] = fmaf(p[i], bf_lo(v.x), o[0]); o[1] = fmaf(p[i], bf_hi(v.x), o[1]);
            o[2] = fmaf(p[i], bf_lo(v.y), o[2]); o[3] = fmaf(p[i], bf_hi(v.y), o[3]);
            o[4] = fmaf(p[i], bf_lo(v.z), o[4]); o[5] = fmaf(p[i], bf_hi(v.z), o[5]);
            o[6] = fmaf(p[i], bf_lo(v.w), o[6]); o[7] = fmaf(p[i], bf_hi(v.w), o[7]);
        }
        __syncwarp();
        if (lane == 0) mbar_arrive(bar_empty + st * 8);
        if (++st == NS) { st = 0; ph ^= 1; }
    }
    PROF(tid == 0, 5);
    *reinterpret_cast<float4*>(red_b + warp * 256 + lane * 8) = make_float4(o[0], o[1], o[2], o[3]);
    *reinterpret_cast<float4*>(red_b + warp * 256 + lane * 8 + 4) = make_float4(o[4], o[5], o[6], o[7]);
    cbar();
    if (tid < 128) {
        const int dim = (tid >> 4) * 32 + ((tid >> 1) & 1) * 16 + (tid & 1) * 8 + ((tid >> 2) & 3) * 2;
        float s0 = 0.f, s1 = 0.f;
#pragma unroll
        for (int w = 0; w < 8; w++) {
            const float2 p = *reinterpret_cast<const float2*>(red_b + w * 256 + dim);
            s0 += p.x; s1 += p.y;
        }
        st_rlx32(&g_o[par][cta * 128 + tid], enc(pack_bf(s0, s1)));
    }
    PROF(tid == 0, 6);
    if (!tail) return;

    constexpr int S_WO = NT % NS, S_W1 = (NT + 1) % NS, S_W2 = (NT + 2) % NS;
    {
        const uint32_t* src = &g_o[par][(hd * 8 + g) * 128 + warp * 16 + t4 * 4];
        uint4 v = ld_rlx128(src);
        mbar_wait(bar_full + S_WO * 8, (NT / NS) & 1);
        uint4 a[2][4];
#pragma unroll
        for (int s = 0; s < 2; s++) {
            const int row = warp * 32 + s * 16 + (lane >> 4) * 8 + (lane & 7);
#pragma unroll
            for (int mt = 0; mt < 4; mt++)
                a[s][mt] = ldm4t(sb + OFF_RING + S_WO * STAGE + row * 128 + (((mt * 2 + ((lane >> 3) & 1)) ^ (lane & 7)) << 4));
        }
        for (int it = 0; !valid4(v) && it < SPIN_MAX; it++) v = ld_rlx128(src);
        __syncwarp();
        v = dec4(v);
        float acc[4][4] = {};
#pragma unroll
        for (int mt = 0; mt < 4; mt++) mma16816(acc[mt], a[0][mt].x, a[0][mt].y, a[0][mt].z, a[0][mt].w, v.x, v.y);
#pragma unroll
        for (int mt = 0; mt < 4; mt++) mma16816(acc[mt], a[1][mt].x, a[1][mt].y, a[1][mt].z, a[1][mt].w, v.z, v.w);
        float* r2 = sc + (warp * 8 + t4 * 2) * 68 + g;
#pragma unroll
        for (int mt = 0; mt < 4; mt++) {
            r2[mt * 16] = acc[mt][0]; r2[68 + mt * 16] = acc[mt][1];
            r2[mt * 16 + 8] = acc[mt][2]; r2[68 + mt * 16 + 8] = acc[mt][3];
        }
        cbar();
        float s0 = 0.f, s1 = 0.f;
#pragma unroll
        for (int w = 0; w < 8; w++) {
            const float2 p = *reinterpret_cast<const float2*>(sc + (w * 8 + warp) * 68 + lane * 2);
            s0 += p.x; s1 += p.y;
        }
        st_rlx64(g_p2 + ((bj * 16 + warp * 2 + (lane >> 4)) * 16 + hd) * 32 + (lane & 15) * 2,
                 (__float_as_uint(s0) & ~1u) | par, (__float_as_uint(s1) & ~1u) | par);
    }
    PROF(tid == 0, 7);

    const int bg = r & 1, cg = r >> 1;
    uint4 bw1[4], aw2[8];
    {
        const uint32_t* src = &g_h[par][warp * (DM / 2) + lane * 4];
        uint4 v0 = make_uint4(1, 1, 1, 1), v1 = v0;
        if (lane < 28) { v0 = ld_rlx128(src); v1 = ld_rlx128(src + 112); }
        if (warp < 7) {
            mbar_wait(bar_full + S_W1 * 8, ((NT + 1) / NS) & 1);
#pragma unroll
            for (int s = 0; s < 4; s++)
                bw1[s] = ldm4t(sb + OFF_RING + S_W1 * STAGE + (warp * 64 + s * 16 + ((lane >> 3) & 1) * 8 + (lane & 7)) * 32 + (lane >> 4) * 16);
        }
        for (int it = 0; it < SPIN_MAX; it++) {
            const bool k0 = valid4(v0), k1 = valid4(v1);
            if (k0 && k1) break;
            if (!k0) v0 = ld_rlx128(src);
            if (!k1) v1 = ld_rlx128(src + 112);
        }
        __syncwarp();
        PROF(tid == 0, 9);
        v0 = dec4(v0); v1 = dec4(v1);
        if (lane == (cg < 28 ? cg : cg - 28))
            *reinterpret_cast<uint4*>(sp + OFF_M + 64 + warp * 16) = cg < 28 ? v0 : v1;
        layernorm_row(v0, v1, lane, sb + OFF_C + warp * (XP * 2));
    }
    cbar();
    if (warp < 7) {
        float acc[2][4] = {};
#pragma unroll
        for (int p = 0; p < 2; p++) {
            const uint4 a = ldm4(sb + OFF_C + (lane & 7) * (XP * 2) + (warp * 64 + p * 32 + (lane >> 3) * 8) * 2);
            mma16816(acc[0], a.x, 0, a.y, 0, bw1[p * 2].x, bw1[p * 2].y);
            mma16816(acc[1], a.x, 0, a.y, 0, bw1[p * 2].z, bw1[p * 2].w);
            mma16816(acc[0], a.z, 0, a.w, 0, bw1[p * 2 + 1].x, bw1[p * 2 + 1].y);
            mma16816(acc[1], a.z, 0, a.w, 0, bw1[p * 2 + 1].z, bw1[p * 2 + 1].w);
        }
        *reinterpret_cast<float4*>(red_b + (warp * 32 + lane) * 4) = make_float4(acc[0][0], acc[0][1], acc[1][0], acc[1][1]);
    }
    cbar();
    if (warp == 0) {
        float4 s = make_float4(0.f, 0.f, 0.f, 0.f);
#pragma unroll
        for (int w = 0; w < 7; w++) {
            const float4 p = *reinterpret_cast<const float4*>(red_b + (w * 32 + lane) * 4);
            s.x += p.x; s.y += p.y; s.z += p.z; s.w += p.w;
        }
        float f0 = rbf(rbf(s.x) + bf_lo(bias1a)), f1 = rbf(rbf(s.y) + bf_hi(bias1a));
        float f2 = rbf(rbf(s.z) + bf_lo(bias1b)), f3 = rbf(rbf(s.w) + bf_hi(bias1b));
        f0 = f0 > 0.f ? f0 : 0.f; f1 = f1 > 0.f ? f1 : 0.f;
        f2 = f2 > 0.f ? f2 : 0.f; f3 = f3 > 0.f ? f3 : 0.f;
        st_rlx64(&g_g[par][((g >> 2) * NTAIL + r) * 32 + (g & 3) * 8 + t4 * 2],
                 enc(pack_bf(f0 * f0, f1 * f1)), enc(pack_bf(f2 * f2, f3 * f3)));
    }
    PROF(tid == 0, 10);
    if (warp == 7) return;

    {
        const uint32_t* src = &g_g[par][(bg * NTAIL + warp * 16 + (g >> 2) * 8) * 32 + (g & 3) * 8 + t4 * 2];
        uint2 v[8];
#pragma unroll
        for (int s = 0; s < 8; s++) v[s] = ld_rlx64(src + s * 32);
        mbar_wait(bar_full + S_W2 * 8, ((NT + 2) / NS) & 1);
#pragma unroll
        for (int s = 0; s < 8; s++)
            aw2[s] = ldm4t(sb + OFF_RING + S_W2 * STAGE + (warp * 256 + ((lane >> 3) & 1) * 128 + s * 16 + (lane >> 4) * 8 + (lane & 7)) * 16);
        for (int it = 0; it < SPIN_MAX; it++) {
            bool ok = true;
#pragma unroll
            for (int s = 0; s < 8; s++) ok &= (v[s].x != 0 && v[s].y != 0);
            if (ok) break;
#pragma unroll
            for (int s = 0; s < 8; s++) if (v[s].x == 0 || v[s].y == 0) v[s] = ld_rlx64(src + s * 32);
        }
        __syncwarp();
        PROF(tid == 0, 11);
        float acc[2][4] = {};
#pragma unroll
        for (int s = 0; s < 8; s++) mma16816(acc[s & 1], aw2[s].x, aw2[s].y, aw2[s].z, aw2[s].w, ~v[s].x, ~v[s].y);
        float y0 = t4 < 2 ? acc[0][0] + acc[1][0] : acc[0][2] + acc[1][2];
        float y1 = t4 < 2 ? acc[0][1] + acc[1][1] : acc[0][3] + acc[1][3];
        y0 += __shfl_xor_sync(0xffffffffu, y0, 2);
        y1 += __shfl_xor_sync(0xffffffffu, y1, 2);
        if (t4 < 2) { sc[warp * 32 + t4 * 16 + g] = y0; sc[warp * 32 + t4 * 16 + 8 + g] = y1; }
        asm volatile("bar.sync 2, 224;" ::: "memory");
        if (warp == 0) {
            float y = 0.f;
#pragma unroll
            for (int w = 0; w < 7; w++) y += sc[w * 32 + lane];
            const int b = bg * 4 + (lane >> 3);
            const float bias2 = (lane & 1) ? bf_hi(bias2w) : bf_lo(bias2w);
            const float hres = __bfloat162float(reinterpret_cast<const __nv_bfloat16*>(sp + OFF_M + 64)[b * 8 + (lane & 7)]);
            out[b * DM + cg * 8 + (lane & 7)] = __float2bfloat16_rn(hres + rbf(rbf(y) + bias2));
            if (cta == 0 && lane == 0) st_rlx32(&g_epoch, epoch);
        }
    }
    PROF(tid == 0, 12);
}

typedef CUresult (*EncodeTiledFn)(CUtensorMap*, CUtensorMapDataType, cuuint32_t, void*, const cuuint64_t*,
                                  const cuuint64_t*, const cuuint32_t*, const cuuint32_t*, CUtensorMapInterleave,
                                  CUtensorMapSwizzle, CUtensorMapL2promotion, CUtensorMapFloatOOBfill);

void encode_2d(EncodeTiledFn fn, CUtensorMap* tm, void* base, int rows, int cols, int box_rows, int box_cols,
               CUtensorMapSwizzle sw) {
    cuuint64_t dims[2] = {(cuuint64_t)cols, (cuuint64_t)rows};
    cuuint64_t strides[1] = {(cuuint64_t)cols * 2};
    cuuint32_t box[2] = {(cuuint32_t)box_cols, (cuuint32_t)box_rows};
    cuuint32_t es[2] = {1, 1};
    fn(tm, CU_TENSOR_MAP_DATA_TYPE_BFLOAT16, 2, base, dims, strides, box, es, CU_TENSOR_MAP_INTERLEAVE_NONE, sw,
       CU_TENSOR_MAP_L2_PROMOTION_L2_128B, CU_TENSOR_MAP_FLOAT_OOB_FILL_NONE);
}

}

extern "C" void kernel_launch(void* const* d_in, const int* in_sizes, int n_in, void* d_out, int out_size) {
    (void)in_sizes; (void)n_in; (void)out_size;
    static EncodeTiledFn encode = nullptr;
    if (!encode) {
        void* fn = nullptr;
        cudaDriverEntryPointQueryResult qr;
        cudaGetDriverEntryPoint("cuTensorMapEncodeTiled", &fn, cudaEnableDefault, &qr);
        encode = (EncodeTiledFn)fn;
        cudaFuncSetAttribute(fused_decode_kernel, cudaFuncAttributeMaxDynamicSharedMemorySize, SMEM_BYTES);
    }
    CUtensorMap tm_wo, tm_w1, tm_w2;
    encode_2d(encode, &tm_wo, d_in[4], NH * DH, DM, 256, 64, CU_TENSOR_MAP_SWIZZLE_128B);
    encode_2d(encode, &tm_w1, d_in[6], DM, FF, 224, 16, CU_TENSOR_MAP_SWIZZLE_NONE);
    encode_2d(encode, &tm_w2, d_in[8], FF, DM, 256, 8, CU_TENSOR_MAP_SWIZZLE_NONE);
    fused_decode_kernel<<<NCTA, NTHREADS, SMEM_BYTES, cudaStreamPerThread>>>(
        (const __nv_bfloat16*)d_in[0], (const __nv_bfloat16*)d_in[1], (const __nv_bfloat16*)d_in[2],
        (const __nv_bfloat16*)d_in[3], (const __nv_bfloat16*)d_in[7], (const __nv_bfloat16*)d_in[9],
        (__nv_bfloat16*)d_out, tm_wo, tm_w1, tm_w2);
}
```

```cpp
#include <cuda_runtime.h>
#include <cuda_bf16.h>
#include <cuda.h>
#include <stdint.h>

namespace {

constexpr int NB = 8, DM = 448, NH = 16, SK = 4096, DH = 256, FF = 1792;
constexpr int NCTA = NB * NH;
constexpr int NTAIL = 112;
constexpr int TILE_KEYS = 32;
constexpr int STAGE = TILE_KEYS * DH * 2;
constexpr int NS = 131072 / STAGE;
constexpr int KT = SK / TILE_KEYS;
constexpr int NT = 2 * KT;
constexpr int NTHREADS = 288;
constexpr int XP = 456;
constexpr int SPIN_MAX = 1 << 22;
#define D0 3
#define WO_AT 0
#define W1_AT 0
#define W2_AT 0
#define ROT 0
#define GATE_H 1
#define GATE_G 0
#define DRY 1

constexpr int OFF_RING = 0;
constexpr int OFF_WO = OFF_RING + NS * STAGE;
constexpr int OFF_W1 = OFF_WO + DH * 128;
constexpr int OFF_W2 = OFF_W1 + DM * 32;
constexpr int OFF_A = OFF_W2 + FF * 16;
constexpr int OFF_B = OFF_A + SK * 2;
constexpr int OFF_C = OFF_B + 9216;
constexpr int OFF_M = OFF_C + NB * XP * 2;
constexpr int OFF_BAR = OFF_M + 256;
constexpr int SMEM_BYTES = OFF_BAR + (2 * NS + 3) * 8;
static_assert(SMEM_BYTES <= 232448, "shared memory budget");

__device__ uint32_t g_epoch;
__device__ __align__(128) uint32_t g_q[2][NB * NH * DH / 2];
__device__ __align__(128) uint32_t g_o[2][NH * NB * DH / 2];
__device__ __align__(128) uint32_t g_h[2][NB * DM / 2];
__device__ __align__(128) uint32_t g_g[2][2 * NTAIL * 32];
__device__ __align__(128) uint32_t g_p2[7 * 16 * 16 * 32];

#define PROF(cond, i)

#define PROFT(cond, i)

__device__ __forceinline__ uint32_t smem_u32(const void* p) { return (uint32_t)__cvta_generic_to_shared(p); }

__device__ __forceinline__ void mbar_init(uint32_t a, uint32_t c) {
    asm volatile("mbarrier.init.shared.b64 [%0], %1;" :: "r"(a), "r"(c) : "memory");
}
__device__ __forceinline__ void mbar_expect_tx(uint32_t a, uint32_t bytes) {
    asm volatile("mbarrier.arrive.expect_tx.shared.b64 _, [%0], %1;" :: "r"(a), "r"(bytes) : "memory");
}
__device__ __forceinline__ void mbar_arrive(uint32_t a) {
    asm volatile("mbarrier.arrive.shared.b64 _, [%0];" :: "r"(a) : "memory");
}
__device__ __forceinline__ void mbar_arrive2(uint32_t a) {
    asm volatile("mbarrier.arrive.shared.b64 _, [%0], 2;" :: "r"(a) : "memory");
}
__device__ __forceinline__ void mbar_wait(uint32_t a, uint32_t parity) {
    uint32_t ok;
    int it = 0;
    do {
        asm volatile("{\n.reg .pred p;\nmbarrier.try_wait.parity.shared.b64 p, [%1], %2;\nselp.u32 %0, 1, 0, p;\n}"
                     : "=r"(ok) : "r"(a), "r"(parity) : "memory");
    } while (!ok && ++it < SPIN_MAX);
}
__device__ __forceinline__ void tma_tile(uint32_t dst, const CUtensorMap* tm, int group, uint32_t bar, uint64_t pol) {
    asm volatile("cp.async.bulk.tensor.4d.shared::cluster.global.mbarrier::complete_tx::bytes.L2::cache_hint"
                 " [%0], [%1, {%3, %3, %3, %4}], [%2], %5;"
                 :: "r"(dst), "l"(tm), "r"(bar), "r"(0), "r"(group), "l"(pol) : "memory");
}
__device__ __forceinline__ void tma_2d(uint32_t dst, const CUtensorMap* tm, int c0, int c1, uint32_t bar) {
    asm volatile("cp.async.bulk.tensor.2d.shared::cluster.global.mbarrier::complete_tx::bytes [%0], [%1, {%3, %4}], [%2];"
                 :: "r"(dst), "l"(tm), "r"(bar), "r"(c0), "r"(c1) : "memory");
}
__device__ __forceinline__ void cbar() { asm volatile("bar.sync 1, 256;" ::: "memory"); }

__device__ __forceinline__ uint4 lds128(uint32_t a) {
    uint4 v;
    asm volatile("ld.shared.v4.u32 {%0,%1,%2,%3}, [%4];" : "=r"(v.x), "=r"(v.y), "=r"(v.z), "=r"(v.w) : "r"(a) : "memory");
    return v;
}
__device__ __forceinline__ uint4 ldm4(uint32_t a) {
    uint4 v;
    asm volatile("ldmatrix.sync.aligned.m8n8.x4.shared.b16 {%0,%1,%2,%3}, [%4];"
                 : "=r"(v.x), "=r"(v.y), "=r"(v.z), "=r"(v.w) : "r"(a) : "memory");
    return v;
}
__device__ __forceinline__ uint4 ldm4t(uint32_t a) {
    uint4 v;
    asm volatile("ldmatrix.sync.aligned.m8n8.x4.trans.shared.b16 {%0,%1,%2,%3}, [%4];"
                 : "=r"(v.x), "=r"(v.y), "=r"(v.z), "=r"(v.w) : "r"(a) : "memory");
    return v;
}
__device__ __forceinline__ void mma16816(float (&c)[4], uint32_t a0, uint32_t a1, uint32_t a2, uint32_t a3, uint32_t b0, uint32_t b1) {
    asm volatile("mma.sync.aligned.m16n8k16.row.col.f32.bf16.bf16.f32 {%0,%1,%2,%3}, {%4,%5,%6,%7}, {%8,%9}, {%0,%1,%2,%3};"
                 : "+f"(c[0]), "+f"(c[1]), "+f"(c[2]), "+f"(c[3])
                 : "r"(a0), "r"(a1), "r"(a2), "r"(a3), "r"(b0), "r"(b1));
}
__device__ __forceinline__ uint4 ld_rlx128(const uint32_t* p) {
    uint4 v;
    asm volatile("ld.relaxed.gpu.global.v4.u32 {%0,%1,%2,%3}, [%4];" : "=r"(v.x), "=r"(v.y), "=r"(v.z), "=r"(v.w) : "l"(p) : "memory");
    return v;
}
__device__ __forceinline__ void ld_rlx128_if(bool c, uint4& v, const uint32_t* p) {
    asm volatile("{\n.reg .pred p;\nsetp.ne.u32 p, %5, 0;\n@p ld.relaxed.gpu.global.v4.u32 {%0,%1,%2,%3}, [%4];\n}"
                 : "+r"(v.x), "+r"(v.y), "+r"(v.z), "+r"(v.w) : "l"(p), "r"((uint32_t)c) : "memory");
}
__device__ __forceinline__ uint2 ld_rlx64(const uint32_t* p) {
    uint2 v;
    asm volatile("ld.relaxed.gpu.global.v2.u32 {%0,%1}, [%2];" : "=r"(v.x), "=r"(v.y) : "l"(p) : "memory");
    return v;
}
__device__ __forceinline__ uint32_t ldg32_now(const void* p) {
    uint32_t v;
    asm volatile("ld.global.nc.u32 %0, [%1];" : "=r"(v) : "l"(p) : "memory");
    return v;
}
__device__ __forceinline__ void st_rlx32(uint32_t* p, uint32_t v) {
    asm volatile("st.relaxed.gpu.global.u32 [%0], %1;" :: "l"(p), "r"(v) : "memory");
}
__device__ __forceinline__ void st_rlx64(uint32_t* p, uint32_t a, uint32_t b) {
    asm volatile("st.relaxed.gpu.global.v2.u32 [%0], {%1,%2};" :: "l"(p), "r"(a), "r"(b) : "memory");
}

__device__ __forceinline__ void st_rlx32_if(bool c, uint32_t* p, uint32_t v) {
    asm volatile("{\n.reg .pred p;\nsetp.ne.u32 p, %2, 0;\n@p st.relaxed.gpu.global.u32 [%0], %1;\n}"
                 :: "l"(p), "r"(v), "r"((uint32_t)c) : "memory");
}
__device__ __forceinline__ void st_rlx64_if(bool c, uint32_t* p, uint32_t a, uint32_t b) {
    asm volatile("{\n.reg .pred p;\nsetp.ne.u32 p, %3, 0;\n@p st.relaxed.gpu.global.v2.u32 [%0], {%1,%2};\n}"
                 :: "l"(p), "r"(a), "r"(b), "r"((uint32_t)c) : "memory");
}

__device__ __forceinline__ void st_rlx128_if(bool c, uint32_t* p, uint32_t a, uint32_t b, uint32_t d, uint32_t e) {
    asm volatile("{\n.reg .pred p;\nsetp.ne.u32 p, %5, 0;\n@p st.relaxed.gpu.global.v4.u32 [%0], {%1,%2,%3,%4};\n}"
                 :: "l"(p), "r"(a), "r"(b), "r"(d), "r"(e), "r"((uint32_t)c) : "memory");
}
__device__ __forceinline__ float bf_lo(uint32_t w) { return __uint_as_float(w << 16); }
__device__ __forceinline__ float bf_hi(uint32_t w) { return __uint_as_float(w & 0xffff0000u); }
__device__ __forceinline__ float rbf(float x) { return __bfloat162float(__float2bfloat16_rn(x)); }
__device__ __forceinline__ uint32_t pack_bf(float lo, float hi) {
    __nv_bfloat162 v = __floats2bfloat162_rn(lo, hi);
    return *reinterpret_cast<uint32_t*>(&v);
}
__device__ __forceinline__ uint32_t enc(uint32_t w) { return w == 0xffffffffu ? 0x80008000u : ~w; }
__device__ __forceinline__ bool valid4(const uint4& v) { return v.x != 0 && v.y != 0 && v.z != 0 && v.w != 0; }
__device__ __forceinline__ uint4 dec4(const uint4& v) { return make_uint4(~v.x, ~v.y, ~v.z, ~v.w); }

__device__ __forceinline__ float warp_sum(float v) {
#pragma unroll
    for (int o = 16; o > 0; o >>= 1) v += __shfl_xor_sync(0xffffffffu, v, o);
    return v;
}

__device__ __forceinline__ void layernorm_row(const uint4& r0, const uint4& r1, int lane, uint32_t dst_row) {
    const bool act = lane < 28;
    float v[16];
    const uint32_t w[8] = {r0.x, r0.y, r0.z, r0.w, r1.x, r1.y, r1.z, r1.w};
#pragma unroll
    for (int i = 0; i < 8; i++) { v[2 * i] = act ? bf_lo(w[i]) : 0.f; v[2 * i + 1] = act ? bf_hi(w[i]) : 0.f; }
    float s = 0.f;
#pragma unroll
    for (int i = 0; i < 16; i++) s += v[i];
    const float mean = warp_sum(s) * (1.0f / DM);
    float q = 0.f;
#pragma unroll
    for (int i = 0; i < 16; i++) { const float d = v[i] - mean; q = fmaf(d, d, q); }
    const float var = warp_sum(act ? q : 0.f) * (1.0f / DM);
    const float mb = rbf(mean);
    const float sd = rbf(sqrtf(rbf(rbf(var) + 1e-5f)));
    const float rs = 1.0f / sd;
    uint32_t o[8];
#pragma unroll
    for (int i = 0; i < 8; i++) o[i] = pack_bf(rbf(v[2 * i] - mb) * rs, rbf(v[2 * i + 1] - mb) * rs);
    if (act) {
        asm volatile("st.shared.v4.u32 [%0], {%1,%2,%3,%4};" :: "r"(dst_row + lane * 16), "r"(o[0]), "r"(o[1]), "r"(o[2]), "r"(o[3]) : "memory");
        asm volatile("st.shared.v4.u32 [%0], {%1,%2,%3,%4};" :: "r"(dst_row + 448 + lane * 16), "r"(o[4]), "r"(o[5]), "r"(o[6]), "r"(o[7]) : "memory");
    }
}

template <class T> __device__ __forceinline__ T* pin(T* p) { asm volatile("" : "+l"(p)); return p; }
__device__ __forceinline__ uint32_t pin(uint32_t v) { asm volatile("" : "+r"(v)); return v; }
__device__ __forceinline__ void sts32(uint32_t a, float v) { asm volatile("st.shared.f32 [%0], %1;" :: "r"(a), "f"(v) : "memory"); }
__device__ __forceinline__ void sts64(uint32_t a, float x, float y) {
    asm volatile("st.shared.v2.f32 [%0], {%1,%2};" :: "r"(a), "f"(x), "f"(y) : "memory");
}
__device__ __forceinline__ void sts128(uint32_t a, float x, float y, float z, float w) {
    asm volatile("st.shared.v4.f32 [%0], {%1,%2,%3,%4};" :: "r"(a), "f"(x), "f"(y), "f"(z), "f"(w) : "memory");
}
__device__ __forceinline__ float lds32f(uint32_t a) {
    float v;
    asm volatile("ld.shared.f32 %0, [%1];" : "=f"(v) : "r"(a) : "memory");
    return v;
}
__device__ __forceinline__ float2 lds64f(uint32_t a) {
    float2 v;
    asm volatile("ld.shared.v2.f32 {%0,%1}, [%2];" : "=f"(v.x), "=f"(v.y) : "r"(a) : "memory");
    return v;
}
__device__ __forceinline__ float4 lds128f(uint32_t a) {
    float4 v;
    asm volatile("ld.shared.v4.f32 {%0,%1,%2,%3}, [%4];" : "=f"(v.x), "=f"(v.y), "=f"(v.z), "=f"(v.w) : "r"(a) : "memory");
    return v;
}
__device__ __forceinline__ bool missing(const uint4& v) { return min(__vimin3_u32(v.x, v.y, v.z), v.w) == 0; }
__device__ __forceinline__ bool stale(const uint4& v, uint32_t tag) {
    return (((v.x ^ tag) | (v.y ^ tag) | (v.z ^ tag) | (v.w ^ tag)) & 1) != 0;
}

__global__ void __launch_bounds__(NTHREADS, 1)
fused_decode_kernel(const __nv_bfloat16* __restrict__ x, const __nv_bfloat16* __restrict__ wq,
                    const __nv_bfloat16* __restrict__ b1, const __nv_bfloat16* __restrict__ b2,
                    __nv_bfloat16* __restrict__ out,
                    const __grid_constant__ CUtensorMap tm_k, const __grid_constant__ CUtensorMap tm_v,
                    const __grid_constant__ CUtensorMap tm_wo, const __grid_constant__ CUtensorMap tm_w1,
                    const __grid_constant__ CUtensorMap tm_w2) {
    extern __shared__ __align__(1024) uint8_t sp[];
    const uint32_t sb = smem_u32(sp);

    const int tid = threadIdx.x, warp = tid >> 5, lane = tid & 31;
    const int cta = blockIdx.x;
    const int hd = cta >> 3, bj = cta & 7;
    const bool tail = bj < 7;
    const int r = hd * 7 + bj;
    const uint32_t bar_full = sb + OFF_BAR, bar_empty = bar_full + NS * 8, bar_w = bar_empty + NS * 8;

    if (warp == 8) {
        const int grp0 = (bj * NH + hd) * (SK / 8);
        const int rot = ROT;
        uint64_t pol;
        asm volatile("createpolicy.fractional.L2::evict_first.b64 %0, 1.0;" : "=l"(pol));
        if (lane == 0) {
            PROF(true, 0);
            asm volatile("prefetch.tensormap [%0];" :: "l"(&tm_k) : "memory");
#pragma unroll
            for (int s = 0; s < NS; s++) { mbar_init(bar_full + s * 8, 1); mbar_init(bar_empty + s * 8, 8); }
#pragma unroll
            for (int s = 0; s < 3; s++) mbar_init(bar_w + s * 8, 1);
            asm volatile("fence.mbarrier_init.release.cluster;" ::: "memory");
#pragma unroll
            for (int s = 0; s < D0; s++) {
                mbar_expect_tx(bar_full + s * 8, STAGE);
                tma_tile(sb + OFF_RING + s * STAGE, &tm_k, grp0 + ((s + rot) & (KT - 1)) * 4, bar_full + s * 8, pol);
            }
        }
        __syncwarp();
        asm volatile("bar.arrive 3, %0;" :: "n"(NTHREADS) : "memory");
        uint32_t epoch;
        asm volatile("ld.relaxed.gpu.global.u32 %0, [%1];" : "=r"(epoch) : "l"(&g_epoch) : "memory");
        const int rb = hd >> 1, blk = bj * 64 + (hd & 1) * 32;
        const int xc = blk + (lane & 1) * 16 + ((lane & 7) >> 1) * 2;
        uint32_t x0 = 0, x1 = 0;
        if (tail) { x0 = ldg32_now(x + rb * DM + xc); x1 = ldg32_now(x + rb * DM + xc + 8); }
        if (lane == 0) {
#pragma unroll 1
            for (int t = D0; t < NS; t++) {
                mbar_wait(bar_full + (t - D0) * 8, 0);
                mbar_expect_tx(bar_full + t * 8, STAGE);
                tma_tile(sb + OFF_RING + t * STAGE, &tm_k, grp0 + ((t + rot) & (KT - 1)) * 4, bar_full + t * 8, pol);
            }
            int s = 0, ph = 0;
#pragma unroll 1
            for (int t = NS; t < NT; t++) {
                mbar_wait(bar_empty + s * 8, ph);
                const uint32_t fb = bar_full + s * 8;
                mbar_expect_tx(fb, STAGE);
                tma_tile(sb + OFF_RING + s * STAGE, t < KT ? &tm_k : &tm_v, grp0 + ((t + rot) & (KT - 1)) * 4, fb, pol);
                if (++s == NS) { s = 0; ph ^= 1; }
                if (t == NS) asm volatile("prefetch.tensormap [%0];" :: "l"(&tm_v) : "memory");
                if (tail) {
                    if (t == NS) {
                        asm volatile("prefetch.tensormap [%0];" :: "l"(&tm_wo) : "memory");
                        asm volatile("prefetch.tensormap [%0];" :: "l"(&tm_w1) : "memory");
                        asm volatile("prefetch.tensormap [%0];" :: "l"(&tm_w2) : "memory");
                    }
                    if (t == NT - 1 - WO_AT) {
                        mbar_expect_tx(bar_w, DH * 128);
                        tma_2d(sb + OFF_WO, &tm_wo, bj * 64, hd * DH, bar_w);
                    }
                    if (t == NT - 1 - W1_AT) {
                        mbar_expect_tx(bar_w + 8, DM * 32);
                        tma_2d(sb + OFF_W1, &tm_w1, r * 16, 0, bar_w + 8);
                        tma_2d(sb + OFF_W1 + 224 * 32, &tm_w1, r * 16, 224, bar_w + 8);
                    }
                    if (t == NT - 1 - W2_AT) {
                        mbar_expect_tx(bar_w + 16, FF * 16);
#pragma unroll
                        for (int i = 0; i < 7; i++) tma_2d(sb + OFF_W2 + i * 4096, &tm_w2, (r >> 1) * 8, i * 256, bar_w + 16);
                    }
                }
            }
        }
        __syncwarp();
        if (!tail) return;
        const uint32_t tag = (epoch + 1) & 1;
        const uint32_t* src = pin(g_p2 + ((bj * 16 + hd) * 16 + (lane >> 3)) * 32 + (lane & 7) * 4);
        uint32_t* dst = pin(&g_h[tag][blk * 4 + rb * 16 + (lane & 7) * 2]);
        int live = !DRY;
        for (;;) {
            live = pin(live);
            uint4 v0 = {}, v1 = {}, v2 = {}, v3 = {};
            bool m0 = live, m1 = live, m2 = live, m3 = live;
            int it = 0;
#pragma unroll 1
            do {
                ld_rlx128_if(m0, v0, src);
                ld_rlx128_if(m1, v1, src + 128);
                ld_rlx128_if(m2, v2, src + 256);
                ld_rlx128_if(m3, v3, src + 384);
                m0 = m0 && stale(v0, tag); m1 = m1 && stale(v1, tag);
                m2 = m2 && stale(v2, tag); m3 = m3 && stale(v3, tag);
            } while (__any_sync(0xffffffffu, m0 || m1 || m2 || m3) && ++it < SPIN_MAX);
            PROF(lane == 0, 8);
            float a0 = (__uint_as_float(v0.x) + __uint_as_float(v1.x)) + (__uint_as_float(v2.x) + __uint_as_float(v3.x));
            float a1 = (__uint_as_float(v0.y) + __uint_as_float(v1.y)) + (__uint_as_float(v2.y) + __uint_as_float(v3.y));
            float a2 = (__uint_as_float(v0.z) + __uint_as_float(v1.z)) + (__uint_as_float(v2.z) + __uint_as_float(v3.z));
            float a3 = (__uint_as_float(v0.w) + __uint_as_float(v1.w)) + (__uint_as_float(v2.w) + __uint_as_float(v3.w));
#pragma unroll
            for (int o = 8; o <= 16; o <<= 1) {
                a0 += __shfl_xor_sync(0xffffffffu, a0, o);
                a1 += __shfl_xor_sync(0xffffffffu, a1, o);
                a2 += __shfl_xor_sync(0xffffffffu, a2, o);
                a3 += __shfl_xor_sync(0xffffffffu, a3, o);
            }
            const uint32_t r0 = pack_bf(a0, a1), r1 = pack_bf(a2, a3);
            const uint32_t h0 = enc(pack_bf(bf_lo(x0) + bf_lo(r0), bf_hi(x0) + bf_hi(r0)));
            const uint32_t h1 = enc(pack_bf(bf_lo(x1) + bf_lo(r1), bf_hi(x1) + bf_hi(r1)));
            st_rlx64_if(lane < 8 && live, dst, h0, h1);
            if (live) {
                if (GATE_H) asm volatile("bar.arrive 5, 256;" ::: "memory");
                return;
            }
            live = 1;
        }
    }

    const int g = lane >> 2, t4 = lane & 3;
    const uint32_t s_wq = sb + OFF_WO;
    {
        const int row = tid >> 2, ch = tid & 3;
        const uint32_t d = s_wq + row * 64 + ((ch ^ ((row >> 1) & 3)) << 4);
        const __nv_bfloat16* p = wq + (size_t)row * (NH * DH) + cta * 32 + ch * 8;
#pragma unroll
        for (int i = 0; i < 7; i++)
            asm volatile("cp.async.cg.shared.global.L2::128B [%0], [%1], 16;"
                         :: "r"(d + i * 4096), "l"(p + (size_t)i * 64 * (NH * DH)) : "memory");
    }
    asm volatile("cp.async.commit_group;" ::: "memory");
    uint4 xr0 = make_uint4(0, 0, 0, 0), xr1 = xr0;
    if (lane < 28) {
        xr0 = *reinterpret_cast<const uint4*>(x + warp * DM + lane * 8);
        xr1 = *reinterpret_cast<const uint4*>(x + warp * DM + 224 + lane * 8);
    }
    uint32_t epoch;
    asm volatile("ld.relaxed.gpu.global.u32 %0, [%1];" : "=r"(epoch) : "l"(&g_epoch) : "memory");
    epoch += 1;
    const uint32_t par = epoch & 1;
    const int bg = r & 1, cg = r >> 1;
    uint32_t bias1a = 0, bias1b = 0, bias2w = 0;
    if (warp == 7 && tail) {
        bias1a = ldg32_now(b1 + r * 16 + t4 * 2);
        bias1b = ldg32_now(b1 + r * 16 + 8 + t4 * 2);
        bias2w = ldg32_now(b2 + cg * 8 + (lane & 6));
    }

    layernorm_row(xr0, xr1, lane, sb + OFF_C + warp * (XP * 2));
    asm volatile("cp.async.wait_group 0;" ::: "memory");
    asm volatile("bar.sync 3, %0;" :: "n"(NTHREADS) : "memory");

    float* red_b = reinterpret_cast<float*>(sp + OFF_B);
    if (warp < 7) {
        float acc[4][4] = {};
#pragma unroll
        for (int p = 0; p < 2; p++) {
            const uint4 a = ldm4(sb + OFF_C + (lane & 7) * (XP * 2) + (warp * 64 + p * 32 + (lane >> 3) * 8) * 2);
#pragma unroll
            for (int s = 0; s < 2; s++) {
                const int row = warp * 64 + p * 32 + s * 16 + ((lane >> 3) & 1) * 8 + (lane & 7);
#pragma unroll
                for (int np = 0; np < 2; np++) {
                    const int ch = np * 2 + (lane >> 4);
                    const uint4 bw = ldm4t(s_wq + row * 64 + ((ch ^ ((row >> 1) & 3)) << 4));
                    mma16816(acc[np * 2], s ? a.z : a.x, 0, s ? a.w : a.y, 0, bw.x, bw.y);
                    mma16816(acc[np * 2 + 1], s ? a.z : a.x, 0, s ? a.w : a.y, 0, bw.z, bw.w);
                }
            }
        }
#pragma unroll
        for (int n = 0; n < 4; n++)
            *reinterpret_cast<float2*>(red_b + (warp * 8 + g) * 40 + n * 8 + t4 * 2) = make_float2(acc[n][0], acc[n][1]);
    }
    cbar();
    if (tid < 128) {
        const int b = tid >> 4, wd = tid & 15;
        float s0 = 0.f, s1 = 0.f;
#pragma unroll
        for (int w = 0; w < 7; w++) {
            const float2 p = *reinterpret_cast<const float2*>(red_b + (w * 8 + b) * 40 + wd * 2);
            s0 += p.x; s1 += p.y;
        }
        st_rlx32(&g_q[par][b * (NH * DH / 2) + cta * 16 + (wd & 3) * 4 + ((wd >> 2) & 1) * 2 + (wd >> 3)], enc(pack_bf(s0, s1)));
    } else {
        const int i = tid - 128;
        g_q[par ^ 1][(i >> 4) * (NH * DH / 2) + cta * 16 + (i & 15)] = 0;
        g_o[par ^ 1][cta * 128 + i] = 0;
        if (tail && i < 64) g_g[par ^ 1][((i >> 5) * NTAIL + r) * 32 + (i & 31)] = 0;
        if (tail && i < 16) g_h[par ^ 1][(bj * 2 + (hd & 1)) * 128 + (hd >> 1) * 16 + i] = 0;
    }
    PROF(tid == 0, 1);
    asm volatile("fence.proxy.async.shared::cta;" ::: "memory");

    uint32_t* const p_o_st = pin(&g_o[par][cta * 128 + warp * 16 + t4 * 4]);
    const uint32_t* const p_o_ld = pin(&g_o[par][(hd * 8 + g) * 128 + warp * 16 + t4 * 4]);
    uint32_t* const p_p2_st = pin(g_p2 + ((bj * 16 + warp * 2 + (lane >> 4)) * 16 + hd) * 32 + (lane & 15) * 2);
    const uint32_t* const p_h_ld = pin(&g_h[par][warp * 256 + lane * 4]);
    uint32_t* const p_g_st = pin(&g_g[par][((g >> 2) * NTAIL + r) * 32 + (g & 3) * 8 + t4 * 2]);
    const uint32_t* const p_g_ld =
        pin(&g_g[par][(bg * NTAIL + warp * 16 + (g >> 2) * 8 + (t4 >> 1)) * 32 + (g & 3) * 8 + (t4 & 1) * 4]);
    __nv_bfloat16* const p_out = pin(out + (bg * 4 + (lane >> 3)) * DM + cg * 8 + (lane & 7));
    const uint32_t a_wo = pin(sb + OFF_WO + (warp * 32 + (lane >> 4) * 8 + (lane & 7)) * 128 + ((((lane >> 3) & 1) ^ (lane & 7)) << 4));
    const uint32_t a_w1 = pin(sb + OFF_W1 + (((lane >> 3) & 1) * 8 + (lane & 7)) * 32 + (lane >> 4) * 16);
    const uint32_t a_w2 = pin(sb + OFF_W2 + (warp * 256 + ((lane >> 3) & 1) * 128 + ((lane >> 2) & 1) * 16 + (lane >> 4) * 8 +
                                             ((lane >> 1) & 1) * 4 + (lane & 1)) * 16);
    const uint32_t o_r2w = pin((uint32_t)(((warp * 8 + t4 * 2) * 68 + g) * 4));
    const uint32_t o_r2r = pin((uint32_t)((warp * 68 + (lane >> 4) * 32 + ((lane >> 1) & 1) * 16 + (lane & 1) * 8 + ((lane >> 2) & 3) * 2) * 4));
    const uint32_t a_r4 = pin(sb + OFF_C + lane * 16);
    const uint32_t a_st = pin(sb + OFF_C + 4096 + g * 8);
    const uint32_t a_r5 = pin(sb + OFF_C + 5120 + (warp < 7 ? warp * 128 + ((t4 & 1) * 16 + g) * 4 : lane * 4));
    const uint32_t a_hres = pin(sb + OFF_M + 64 + (warp < 7 ? lane * 4 : (bg * 4 + (lane >> 3)) * 16 + (lane & 7) * 2));
    __nv_bfloat16* sc = reinterpret_cast<__nv_bfloat16*>(sp + OFF_A);

    int live = !DRY;
    for (;;) {
        live = pin(live);
        float oa[4][4] = {}, ob[4][4] = {};
        if (live) {
            uint4 q[8];
            {
                const uint32_t* src = &g_q[par][bj * (NH * DH / 2) + hd * (DH / 2) + lane * 4];
                uint4 v = {};
#pragma unroll 1
                for (int it = 0; __any_sync(0xffffffffu, missing(v)) && it < SPIN_MAX; it++) ld_rlx128_if(missing(v), v, src);
                uint4* qs = reinterpret_cast<uint4*>(sp + OFF_A + warp * 512);
                qs[lane] = dec4(v);
                __syncwarp();
#pragma unroll
                for (int i = 0; i < 8; i++) q[i] = qs[i * 4 + t4];
                cbar();
            }
            PROF(tid == 0, 2);

            float mx = -INFINITY;
            {
                const uint32_t ka = sb + OFF_RING + (warp & 3) * 4096 + (lane & 7) * 128 + (((lane >> 3) ^ (lane & 7)) << 4);
                uint32_t* scw = reinterpret_cast<uint32_t*>(sc) + t4 * 4 + (warp & 1) * 2 + ((warp >> 1) & 1);
#pragma unroll 1
                for (int t = warp >> 2; t < KT; t += 2) {
                    const int st = t & (NS - 1);
                    mbar_wait(bar_full + st * 8, (t / NS) & 1);
                    PROFT(lane == 0 && (warp & 3) == 0, t);
                    uint4 kf[8];
#pragma unroll
                    for (int i = 0; i < 8; i++) kf[i] = ldm4((ka ^ ((i & 1) << 6)) + st * STAGE + (i >> 1) * 1024);
                    float c[4][4] = {};
#pragma unroll
                    for (int i = 0; i < 8; i++) {
                        mma16816(c[(i & 1) * 2], q[i].x, q[i].y, q[i].z, q[i].w, kf[i].x, kf[i].y);
                        mma16816(c[(i & 1) * 2 + 1], q[i].x, q[i].y, q[i].z, q[i].w, kf[i].z, kf[i].w);
                    }
                    if (lane == 0) mbar_arrive2(bar_empty + st * 8);
                    const uint32_t d = pack_bf((c[0][0] + c[2][0]) + (c[1][2] + c[3][2]), (c[0][1] + c[2][1]) + (c[1][3] + c[3][3]));
                    const uint32_t sw = pack_bf(bf_lo(d) * 0.0625f, bf_hi(d) * 0.0625f);
                    mx = fmaxf(mx, fmaxf(bf_lo(sw), bf_hi(sw)));
                    if (lane < 4) scw[t * 16] = sw;
                }
            }
            PROF(tid == 0, 3);

            float* sm_m = reinterpret_cast<float*>(sp + OFF_M);
            mx = fmaxf(mx, __shfl_xor_sync(0xffffffffu, mx, 1));
            mx = fmaxf(mx, __shfl_xor_sync(0xffffffffu, mx, 2));
            if (lane == 0) sm_m[warp] = mx;
            cbar();
#pragma unroll
            for (int w = 0; w < 8; w++) mx = fmaxf(mx, sm_m[w]);
            {
                float e[16], sum = 0.f;
#pragma unroll
                for (int i = 0; i < 4; i++) {
                    const uint2 s = *reinterpret_cast<const uint2*>(sc + i * 1024 + tid * 4);
                    e[i * 4 + 0] = expf(bf_lo(s.x) - mx); e[i * 4 + 1] = expf(bf_hi(s.x) - mx);
                    e[i * 4 + 2] = expf(bf_lo(s.y) - mx); e[i * 4 + 3] = expf(bf_hi(s.y) - mx);
                    sum += (e[i * 4] + e[i * 4 + 1]) + (e[i * 4 + 2] + e[i * 4 + 3]);
                }
                sum = warp_sum(sum);
                if (lane == 0) sm_m[8 + warp] = sum;
                cbar();
                sum = 0.f;
#pragma unroll
                for (int w = 0; w < 8; w++) sum += sm_m[8 + w];
                const float inv = 1.0f / sum;
#pragma unroll
                for (int i = 0; i < 4; i++)
                    *reinterpret_cast<uint2*>(sc + i * 1024 + tid * 4) =
                        make_uint2(pack_bf(e[i * 4] * inv, e[i * 4 + 1] * inv), pack_bf(e[i * 4 + 2] * inv, e[i * 4 + 3] * inv));
                cbar();
            }
            PROF(tid == 0, 4);

            const uint32_t va = sb + OFF_RING + ((lane >> 3) & 1) * 4096 + (warp >> 1) * 1024 + (lane & 7) * 128 +
                                ((((warp & 1) * 4 + (lane >> 4)) ^ (lane & 7)) << 4);
#pragma unroll 1
            for (int t = 0; t < KT; t++) {
                const int st = t & (NS - 1);
                const uint4 p = lds128(sb + OFF_A + t * 64 + t4 * 16);
                mbar_wait(bar_full + st * 8, ((KT + t) / NS) & 1);
                PROFT(tid == 0, KT + t);
                const uint4 v0 = ldm4t(va + st * STAGE), v1 = ldm4t((va ^ 32) + st * STAGE);
                const uint4 v2 = ldm4t(va + st * STAGE + 8192), v3 = ldm4t((va ^ 32) + st * STAGE + 8192);
                mma16816(oa[0], p.x, p.y, p.z, p.w, v0.x, v0.y);
                mma16816(oa[1], p.x, p.y, p.z, p.w, v0.z, v0.w);
                mma16816(oa[2], p.x, p.y, p.z, p.w, v1.x, v1.y);
                mma16816(oa[3], p.x, p.y, p.z, p.w, v1.z, v1.w);
                mma16816(ob[0], p.x, p.y, p.z, p.w, v2.x, v2.y);
                mma16816(ob[1], p.x, p.y, p.z, p.w, v2.z, v2.w);
                mma16816(ob[2], p.x, p.y, p.z, p.w, v3.x, v3.y);
                mma16816(ob[3], p.x, p.y, p.z, p.w, v3.z, v3.w);
                if (lane == 0) mbar_arrive(bar_empty + st * 8);
            }
            PROF(tid == 0, 5);
        }

        st_rlx128_if(live && lane < 4, p_o_st,
                     enc(pack_bf(oa[0][0] + ob[0][2], oa[0][1] + ob[0][3])), enc(pack_bf(oa[1][0] + ob[1][2], oa[1][1] + ob[1][3])),
                     enc(pack_bf(oa[2][0] + ob[2][2], oa[2][1] + ob[2][3])), enc(pack_bf(oa[3][0] + ob[3][2], oa[3][1] + ob[3][3])));
        PROF(tid == 0, 6);
        if (!tail) { if (live) return; live = 1; continue; }

        {
            const uint32_t red_a = sb + (live ? OFF_RING + ((NT - 3) % NS) * STAGE : OFF_W2);
            uint4 v = make_uint4(1, 1, 1, 1);
            if (live) {
                v = ld_rlx128(p_o_ld);
                mbar_wait(bar_w, 0);
                mbar_wait(bar_empty + ((NT - 3) % NS) * 8, ((NT - 3) / NS) & 1);
                mbar_wait(bar_empty + ((NT - 2) % NS) * 8, ((NT - 2) / NS) & 1);
            }
            uint4 a[2][4];
#pragma unroll
            for (int s = 0; s < 2; s++)
#pragma unroll
                for (int mt = 0; mt < 4; mt++) a[s][mt] = ldm4t((a_wo ^ (mt << 5)) + s * 2048);
#pragma unroll 1
            for (int it = 0; __any_sync(0xffffffffu, missing(v)) && it < SPIN_MAX; it++) ld_rlx128_if(missing(v), v, p_o_ld);
            v = dec4(v);
            float acc[4][4] = {};
#pragma unroll
            for (int mt = 0; mt < 4; mt++) mma16816(acc[mt], a[0][mt].x, a[0][mt].y, a[0][mt].z, a[0][mt].w, v.x, v.y);
#pragma unroll
            for (int mt = 0; mt < 4; mt++) mma16816(acc[mt], a[1][mt].x, a[1][mt].y, a[1][mt].z, a[1][mt].w, v.z, v.w);
#pragma unroll
            for (int mt = 0; mt < 4; mt++) {
                sts32(red_a + o_r2w + mt * 64, acc[mt][0]);
                sts32(red_a + o_r2w + mt * 64 + 272, acc[mt][1]);
                sts32(red_a + o_r2w + mt * 64 + 32, acc[mt][2]);
                sts32(red_a + o_r2w + mt * 64 + 304, acc[mt][3]);
            }
            cbar();
            float2 p[8];
#pragma unroll
            for (int w = 0; w < 8; w++) p[w] = lds64f(red_a + o_r2r + w * (8 * 272));
            const float s0 = ((p[0].x + p[1].x) + (p[2].x + p[3].x)) + ((p[4].x + p[5].x) + (p[6].x + p[7].x));
            const float s1 = ((p[0].y + p[1].y) + (p[2].y + p[3].y)) + ((p[4].y + p[5].y) + (p[6].y + p[7].y));
            st_rlx64_if(live, p_p2_st, (__float_as_uint(s0) & ~1u) | par, (__float_as_uint(s1) & ~1u) | par);
        }
        PROF(tid == 0, 7);

        constexpr uint32_t ONES = 0x3f803f80u;
        if (warp < 7) {
            uint4 v0 = make_uint4(1, 1, 1, 1), v1 = v0;
            if (live) {
                v0 = ld_rlx128(p_h_ld);
                v1 = ld_rlx128(p_h_ld + 128);
                mbar_wait(bar_w + 8, 0);
            }
            uint4 bw[4];
#pragma unroll
            for (int s = 0; s < 4; s++) bw[s] = ldm4t(a_w1 + warp * 2048 + s * 512);
            if (GATE_H && live) asm volatile("bar.sync 5, 256;" ::: "memory");
#pragma unroll 1
            for (int it = 0; __any_sync(0xffffffffu, missing(v0) || missing(v1)) && it < SPIN_MAX; it++) {
                const bool m0 = missing(v0), m1 = missing(v1);
                ld_rlx128_if(m0, v0, p_h_ld);
                ld_rlx128_if(m1, v1, p_h_ld + 128);
            }
            PROF(tid == 0, 9);
            v0 = dec4(v0); v1 = dec4(v1);
            const uint32_t hw[8] = {v0.x, v0.y, v0.z, v0.w, v1.x, v1.y, v1.z, v1.w};
            float c0[4] = {}, c1[4] = {}, cs[4] = {};
#pragma unroll
            for (int s = 0; s < 4; s++) {
                mma16816(cs, hw[2 * s], ONES, hw[2 * s + 1], ONES, hw[2 * s], hw[2 * s + 1]);
                mma16816(c0, hw[2 * s], ONES, hw[2 * s + 1], ONES, bw[s].x, bw[s].y);
                mma16816(c1, hw[2 * s], ONES, hw[2 * s + 1], ONES, bw[s].z, bw[s].w);
            }
            if (warp == (cg >> 3)) {
                const uint4 hv = (cg & 4) ? v1 : v0;
                const uint32_t hx = (cg & 2) ? ((cg & 1) ? hv.w : hv.z) : ((cg & 1) ? hv.y : hv.x);
                sts32(a_hres, __uint_as_float(hx));
            }
            if (t4 == (g >> 1)) sts64(a_st + warp * 64, (g & 1) ? cs[3] : cs[2], (g & 1) ? cs[1] : cs[0]);
            sts128(a_r4 + warp * 512, c0[0], c0[1], c1[0], c1[1]);
            asm volatile("bar.arrive 2, 256;" ::: "memory");

            uint4 u0 = make_uint4(1, 1, 1, 1), u1 = u0, u2 = u0, u3 = u0;
            if (live) mbar_wait(bar_w + 16, 0);
            uint4 aw[8];
#pragma unroll
            for (int s = 0; s < 8; s++) aw[s] = ldm4t(a_w2 + (s >> 1) * 512 + (s & 1) * 32);
            if (GATE_G) asm volatile("bar.sync 6, 256;" ::: "memory");
            bool m0 = live, m1 = live, m2 = live, m3 = live;
            int it = 0;
#pragma unroll 1
            do {
                ld_rlx128_if(m0, u0, p_g_ld);
                ld_rlx128_if(m1, u1, p_g_ld + 64);
                ld_rlx128_if(m2, u2, p_g_ld + 128);
                ld_rlx128_if(m3, u3, p_g_ld + 192);
                m0 = missing(u0); m1 = missing(u1); m2 = missing(u2); m3 = missing(u3);
            } while (__any_sync(0xffffffffu, m0 || m1 || m2 || m3) && ++it < SPIN_MAX);
            PROF(tid == 0, 11);
            float y0[4] = {}, y1[4] = {}, y2[4] = {}, y3[4] = {};
            mma16816(y0, aw[0].x, aw[0].y, aw[0].z, aw[0].w, u0.x, u0.y);
            mma16816(y1, aw[2].x, aw[2].y, aw[2].z, aw[2].w, u1.x, u1.y);
            mma16816(y2, aw[4].x, aw[4].y, aw[4].z, aw[4].w, u2.x, u2.y);
            mma16816(y3, aw[6].x, aw[6].y, aw[6].z, aw[6].w, u3.x, u3.y);
            mma16816(y0, aw[1].x, aw[1].y, aw[1].z, aw[1].w, u0.z, u0.w);
            mma16816(y1, aw[3].x, aw[3].y, aw[3].z, aw[3].w, u1.z, u1.w);
            mma16816(y2, aw[5].x, aw[5].y, aw[5].z, aw[5].w, u2.z, u2.w);
            mma16816(y3, aw[7].x, aw[7].y, aw[7].z, aw[7].w, u3.z, u3.w);
            const bool lo = t4 < 2;
            const float z0 = ((lo ? y0[0] : y0[2]) + (lo ? y1[0] : y1[2])) + ((lo ? y2[0] : y2[2]) + (lo ? y3[0] : y3[2]));
            const float z1 = ((lo ? y0[1] : y0[3]) + (lo ? y1[1] : y1[3])) + ((lo ? y2[1] : y2[3]) + (lo ? y3[1] : y3[3]));
            sts32(a_r5 + (lo ? 0 : 896), z0);
            sts32(a_r5 + (lo ? 32 : 928), z1);
            asm volatile("bar.arrive 4, 256;" ::: "memory");
        } else {
            float w0[4] = {}, w1s[4] = {}, w2s[4] = {}, w3s[4] = {};
            if (live) mbar_wait(bar_w + 8, 0);
#pragma unroll 1
            for (int s = 0; s < 28; s += 14) {
                uint4 bw[14];
#pragma unroll
                for (int i = 0; i < 14; i++) bw[i] = ldm4t(a_w1 + (s + i) * 512);
#pragma unroll
                for (int i = 0; i < 14; i += 2) {
                    mma16816(w0, ONES, ONES, ONES, ONES, bw[i].x, bw[i].y);
                    mma16816(w1s, ONES, ONES, ONES, ONES, bw[i].z, bw[i].w);
                    mma16816(w2s, ONES, ONES, ONES, ONES, bw[i + 1].x, bw[i + 1].y);
                    mma16816(w3s, ONES, ONES, ONES, ONES, bw[i + 1].z, bw[i + 1].w);
                }
            }
            w0[0] += w2s[0]; w0[1] += w2s[1]; w1s[0] += w3s[0]; w1s[1] += w3s[1];
            asm volatile("bar.sync 2, 256;" ::: "memory");
            float2 sq[7];
            float4 p[7];
#pragma unroll
            for (int w = 0; w < 7; w++) sq[w] = lds64f(a_st + w * 64);
#pragma unroll
            for (int w = 0; w < 7; w++) p[w] = lds128f(a_r4 + w * 512);
            const float mean = (((sq[0].x + sq[1].x) + (sq[2].x + sq[3].x)) + ((sq[4].x + sq[5].x) + sq[6].x)) * (1.0f / DM);
            const float msq = (((sq[0].y + sq[1].y) + (sq[2].y + sq[3].y)) + ((sq[4].y + sq[5].y) + sq[6].y)) * (1.0f / DM);
            const float var = fmaxf(fmaf(-mean, mean, msq), 0.f);
            float sd, rs;
            asm("sqrt.approx.f32 %0, %1;" : "=f"(sd) : "f"(rbf(rbf(var) + 1e-5f)));
            asm("rcp.approx.f32 %0, %1;" : "=f"(rs) : "f"(rbf(sd)));
            const float mb = rbf(mean);
            const float s0 = fmaf(-mb, w0[0], ((p[0].x + p[1].x) + (p[2].x + p[3].x)) + ((p[4].x + p[5].x) + p[6].x));
            const float s1 = fmaf(-mb, w0[1], ((p[0].y + p[1].y) + (p[2].y + p[3].y)) + ((p[4].y + p[5].y) + p[6].y));
            const float s2 = fmaf(-mb, w1s[0], ((p[0].z + p[1].z) + (p[2].z + p[3].z)) + ((p[4].z + p[5].z) + p[6].z));
            const float s3 = fmaf(-mb, w1s[1], ((p[0].w + p[1].w) + (p[2].w + p[3].w)) + ((p[4].w + p[5].w) + p[6].w));
            const uint32_t ra = pack_bf(s0 * rs, s1 * rs), rc = pack_bf(s2 * rs, s3 * rs);
            const uint32_t fa = pack_bf(bf_lo(ra) + bf_lo(bias1a), bf_hi(ra) + bf_hi(bias1a));
            const uint32_t fc = pack_bf(bf_lo(rc) + bf_lo(bias1b), bf_hi(rc) + bf_hi(bias1b));
            const float f0 = fmaxf(bf_lo(fa), 0.f), f1 = fmaxf(bf_hi(fa), 0.f);
            const float f2 = fmaxf(bf_lo(fc), 0.f), f3 = fmaxf(bf_hi(fc), 0.f);
            st_rlx64_if(live, p_g_st, pack_bf(f0 * f0, f1 * f1) | 0x80008000u, pack_bf(f2 * f2, f3 * f3) | 0x80008000u);
            if (GATE_G) asm volatile("bar.arrive 6, 256;" ::: "memory");
            PROF(lane == 0, 10);
            uint16_t hraw;
            asm volatile("ld.shared.u16 %0, [%1];" : "=h"(hraw) : "r"(a_hres) : "memory");
            const float hres = __uint_as_float((uint32_t)hraw << 16);
            const float bias2 = (lane & 1) ? bf_hi(bias2w) : bf_lo(bias2w);
            asm volatile("bar.sync 4, 256;" ::: "memory");
            float y[14];
#pragma unroll
            for (int w = 0; w < 14; w++) y[w] = lds32f(a_r5 + w * 128);
            const float ys = (((y[0] + y[1]) + (y[2] + y[3])) + ((y[4] + y[5]) + (y[6] + y[7]))) +
                             (((y[8] + y[9]) + (y[10] + y[11])) + (y[12] + y[13]));
            const __nv_bfloat16 res = __float2bfloat16_rn(hres + rbf(rbf(-ys) + bias2));
            if (live) *p_out = res;
            if (live && cta == 0 && lane == 0) st_rlx32(&g_epoch, epoch);
            PROF(lane == 0, 12);
        }
        if (live) return;
        live = 1;
        asm volatile("fence.proxy.async.shared::cta;" ::: "memory");
    }
}

typedef CUresult (*EncodeTiledFn)(CUtensorMap*, CUtensorMapDataType, cuuint32_t, void*, const cuuint64_t*,
                                  const cuuint64_t*, const cuuint32_t*, const cuuint32_t*, CUtensorMapInterleave,
                                  CUtensorMapSwizzle, CUtensorMapL2promotion, CUtensorMapFloatOOBfill);

void encode_2d(EncodeTiledFn fn, CUtensorMap* tm, void* base, int rows, int cols, int box_rows, int box_cols,
               CUtensorMapSwizzle sw) {
    cuuint64_t dims[2] = {(cuuint64_t)cols, (cuuint64_t)rows};
    cuuint64_t strides[1] = {(cuuint64_t)cols * 2};
    cuuint32_t box[2] = {(cuuint32_t)box_cols, (cuuint32_t)box_rows};
    cuuint32_t es[2] = {1, 1};
    fn(tm, CU_TENSOR_MAP_DATA_TYPE_BFLOAT16, 2, base, dims, strides, box, es, CU_TENSOR_MAP_INTERLEAVE_NONE, sw,
       CU_TENSOR_MAP_L2_PROMOTION_L2_128B, CU_TENSOR_MAP_FLOAT_OOB_FILL_NONE);
}

void encode_kv(EncodeTiledFn fn, CUtensorMap* tm, void* base) {
    cuuint64_t dims[4] = {64, 8, 4, (cuuint64_t)NB * NH * SK / 8};
    cuuint64_t strides[3] = {DH * 2, 128, 8 * DH * 2};
    cuuint32_t box[4] = {64, 8, 4, TILE_KEYS / 8};
    cuuint32_t es[4] = {1, 1, 1, 1};
    fn(tm, CU_TENSOR_MAP_DATA_TYPE_BFLOAT16, 4, base, dims, strides, box, es, CU_TENSOR_MAP_INTERLEAVE_NONE,
       CU_TENSOR_MAP_SWIZZLE_128B, CU_TENSOR_MAP_L2_PROMOTION_NONE, CU_TENSOR_MAP_FLOAT_OOB_FILL_NONE);
}

}

extern "C" void kernel_launch(void* const* d_in, const int* in_sizes, int n_in, void* d_out, int out_size) {
    (void)in_sizes; (void)n_in; (void)out_size;
    static EncodeTiledFn encode = nullptr;
    if (!encode) {
        void* fn = nullptr;
        cudaDriverEntryPointQueryResult qr;
        cudaGetDriverEntryPoint("cuTensorMapEncodeTiled", &fn, cudaEnableDefault, &qr);
        encode = (EncodeTiledFn)fn;
        cudaFuncSetAttribute(fused_decode_kernel, cudaFuncAttributeMaxDynamicSharedMemorySize, SMEM_BYTES);
    }
    CUtensorMap tm_k, tm_v, tm_wo, tm_w1, tm_w2;
    encode_kv(encode, &tm_k, d_in[1]);
    encode_kv(encode, &tm_v, d_in[2]);
    encode_2d(encode, &tm_wo, d_in[4], NH * DH, DM, 256, 64, CU_TENSOR_MAP_SWIZZLE_128B);
    encode_2d(encode, &tm_w1, d_in[6], DM, FF, 224, 16, CU_TENSOR_MAP_SWIZZLE_NONE);
    encode_2d(encode, &tm_w2, d_in[8], FF, DM, 256, 8, CU_TENSOR_MAP_SWIZZLE_NONE);
    fused_decode_kernel<<<NCTA, NTHREADS, SMEM_BYTES, cudaStreamPerThread>>>(
        (const __nv_bfloat16*)d_in[0], (const __nv_bfloat16*)d_in[3], (const __nv_bfloat16*)d_in[7],
        (const __nv_bfloat16*)d_in[9], (__nv_bfloat16*)d_out, tm_k, tm_v, tm_wo, tm_w1, tm_w2);
}
```

```cpp
#include <cuda_runtime.h>
#include <cuda_bf16.h>
#include <cuda.h>
#include <stdint.h>

namespace {

constexpr int NB = 8, DM = 448, NH = 16, SK = 4096, DH = 256, FF = 1792;
constexpr int NCTA = NB * NH;
constexpr int NTAIL = 112;
constexpr int TILE_KEYS = 32;
constexpr int STAGE = TILE_KEYS * DH * 2;
constexpr int NS = 131072 / STAGE;
constexpr int KT = SK / TILE_KEYS;
constexpr int NT = 2 * KT;
constexpr int NTHREADS = 320;
constexpr int XP = 456;
constexpr int SPIN_MAX = 1 << 22;
#define D0 3
#define WIN 448
#define MINF 3
#define WOA_T 255
#define WOB_T 255
#define REDNT 1
#define OEARLY 4
#define SPRINT 0
#define PFO_T -1
#define X1 0
#define W2_T0 200
#define W2_STEP 4
#define W1_T0 232
#define W1_STEP 4
#define PROF0 288
#define KCYC 0
#define HSLEEP 300
#define ROT cta
#define R1MAP 0
#define W1LATE 0
#define HREP 4
#define GATE_G 0

constexpr int OFF_RING = 0;
constexpr int OFF_WO = OFF_RING + NS * STAGE;
constexpr int OFF_W1 = OFF_WO + DH * 128;
constexpr int OFF_W2 = OFF_W1 + DM * 32;
constexpr int OFF_A = OFF_W2 + FF * 16;
constexpr int OFF_B = OFF_A + SK * 2;
constexpr int OFF_Q = OFF_B + 8960;
constexpr int OFF_C = OFF_Q + 512;
constexpr int OFF_M = OFF_C + NB * XP * 2;
constexpr int OFF_BAR = OFF_M + 256;
constexpr int SMEM_BYTES = OFF_BAR + (2 * NS + 4) * 8;
static_assert(SMEM_BYTES <= 232448, "shared memory budget");

__device__ uint32_t g_epoch;
__device__ __align__(128) uint32_t g_prog[2][32];
__device__ __align__(128) uint32_t g_q[2][NB * NH * DH / 2];
__device__ __align__(128) uint32_t g_o[2][NH * NB * DH / 2];
__device__ __align__(128) uint32_t g_h[2][HREP][NB * DM / 2];
__device__ __align__(128) uint32_t g_g[2][2 * NTAIL * 32];
__device__ __align__(128) uint32_t g_p2[7 * 16 * 16 * 32];

#define PROF(cond, i)
#define CKDECL
#define CK32(i)
#define CKOUT()

__device__ __forceinline__ uint32_t smem_u32(const void* p) { return (uint32_t)__cvta_generic_to_shared(p); }

__device__ __forceinline__ void mbar_init(uint32_t a, uint32_t c) {
    asm volatile("mbarrier.init.shared.b64 [%0], %1;" :: "r"(a), "r"(c) : "memory");
}
__device__ __forceinline__ void mbar_expect_tx(uint32_t a, uint32_t bytes) {
    asm volatile("mbarrier.arrive.expect_tx.shared.b64 _, [%0], %1;" :: "r"(a), "r"(bytes) : "memory");
}
__device__ __forceinline__ void mbar_arrive(uint32_t a) {
    asm volatile("mbarrier.arrive.shared.b64 _, [%0];" :: "r"(a) : "memory");
}
__device__ __forceinline__ void mbar_arrive2(uint32_t a) {
    asm volatile("mbarrier.arrive.shared.b64 _, [%0], 2;" :: "r"(a) : "memory");
}
__device__ __forceinline__ bool mbar_test(uint32_t a, uint32_t parity) {
    uint32_t ok;
    asm volatile("{\n.reg .pred p;\nmbarrier.test_wait.parity.shared.b64 p, [%1], %2;\nselp.u32 %0, 1, 0, p;\n}"
                 : "=r"(ok) : "r"(a), "r"(parity) : "memory");
    return ok;
}
__device__ __forceinline__ uint32_t clock32() {
    uint32_t c;
    asm volatile("mov.u32 %0, %%clock;" : "=r"(c));
    return c;
}
__device__ __forceinline__ void mbar_wait(uint32_t a, uint32_t parity) {
    uint32_t ok;
    int it = 0;
    do {
        asm volatile("{\n.reg .pred p;\nmbarrier.try_wait.parity.shared.b64 p, [%1], %2;\nselp.u32 %0, 1, 0, p;\n}"
                     : "=r"(ok) : "r"(a), "r"(parity) : "memory");
    } while (!ok && ++it < SPIN_MAX);
}
__device__ __forceinline__ void tma_tile(uint32_t dst, const CUtensorMap* tm, int group, uint32_t bar, uint64_t pol) {
    asm volatile("cp.async.bulk.tensor.4d.shared::cluster.global.mbarrier::complete_tx::bytes.L2::cache_hint"
                 " [%0], [%1, {%3, %3, %3, %4}], [%2], %5;"
                 :: "r"(dst), "l"(tm), "r"(bar), "r"(0), "r"(group), "l"(pol) : "memory");
}
__device__ __forceinline__ void tma_2d(uint32_t dst, const CUtensorMap* tm, int c0, int c1, uint32_t bar) {
    asm volatile("cp.async.bulk.tensor.2d.shared::cluster.global.mbarrier::complete_tx::bytes [%0], [%1, {%3, %4}], [%2];"
                 :: "r"(dst), "l"(tm), "r"(bar), "r"(c0), "r"(c1) : "memory");
}
__device__ __forceinline__ void cbar() { asm volatile("bar.sync 1, 256;" ::: "memory"); }

__device__ __forceinline__ uint4 lds128(uint32_t a) {
    uint4 v;
    asm volatile("ld.shared.v4.u32 {%0,%1,%2,%3}, [%4];" : "=r"(v.x), "=r"(v.y), "=r"(v.z), "=r"(v.w) : "r"(a) : "memory");
    return v;
}
__device__ __forceinline__ uint4 ldm4(uint32_t a) {
    uint4 v;
    asm volatile("ldmatrix.sync.aligned.m8n8.x4.shared.b16 {%0,%1,%2,%3}, [%4];"
                 : "=r"(v.x), "=r"(v.y), "=r"(v.z), "=r"(v.w) : "r"(a) : "memory");
    return v;
}
__device__ __forceinline__ uint4 ldm4t(uint32_t a) {
    uint4 v;
    asm volatile("ldmatrix.sync.aligned.m8n8.x4.trans.shared.b16 {%0,%1,%2,%3}, [%4];"
                 : "=r"(v.x), "=r"(v.y), "=r"(v.z), "=r"(v.w) : "r"(a) : "memory");
    return v;
}
__device__ __forceinline__ void mma16816(float (&c)[4], uint32_t a0, uint32_t a1, uint32_t a2, uint32_t a3, uint32_t b0, uint32_t b1) {
    asm volatile("mma.sync.aligned.m16n8k16.row.col.f32.bf16.bf16.f32 {%0,%1,%2,%3}, {%4,%5,%6,%7}, {%8,%9}, {%0,%1,%2,%3};"
                 : "+f"(c[0]), "+f"(c[1]), "+f"(c[2]), "+f"(c[3])
                 : "r"(a0), "r"(a1), "r"(a2), "r"(a3), "r"(b0), "r"(b1));
}
__device__ __forceinline__ uint4 ld_rlx128(const uint32_t* p) {
    uint4 v;
    asm volatile("ld.relaxed.gpu.global.v4.u32 {%0,%1,%2,%3}, [%4];" : "=r"(v.x), "=r"(v.y), "=r"(v.z), "=r"(v.w) : "l"(p) : "memory");
    return v;
}
__device__ __forceinline__ void ld_rlx128_if(bool c, uint4& v, const uint32_t* p) {
    asm volatile("{\n.reg .pred p;\nsetp.ne.u32 p, %5, 0;\n@p ld.relaxed.gpu.global.v4.u32 {%0,%1,%2,%3}, [%4];\n}"
                 : "+r"(v.x), "+r"(v.y), "+r"(v.z), "+r"(v.w) : "l"(p), "r"((uint32_t)c) : "memory");
}
__device__ __forceinline__ uint32_t ldg32_now(const void* p) {
    uint32_t v;
    asm volatile("ld.global.nc.u32 %0, [%1];" : "=r"(v) : "l"(p) : "memory");
    return v;
}
__device__ __forceinline__ uint4 ldg128_now(const void* p) {
    uint4 v;
    asm volatile("ld.global.nc.v4.u32 {%0,%1,%2,%3}, [%4];" : "=r"(v.x), "=r"(v.y), "=r"(v.z), "=r"(v.w) : "l"(p) : "memory");
    return v;
}
__device__ __forceinline__ void st_rlx32(uint32_t* p, uint32_t v) {
    asm volatile("st.relaxed.gpu.global.u32 [%0], %1;" :: "l"(p), "r"(v) : "memory");
}
__device__ __forceinline__ void st_rlx64(uint32_t* p, uint32_t a, uint32_t b) {
    asm volatile("st.relaxed.gpu.global.v2.u32 [%0], {%1,%2};" :: "l"(p), "r"(a), "r"(b) : "memory");
}

__device__ __forceinline__ void st_rlx32_if(bool c, uint32_t* p, uint32_t v) {
    asm volatile("{\n.reg .pred p;\nsetp.ne.u32 p, %2, 0;\n@p st.relaxed.gpu.global.u32 [%0], %1;\n}"
                 :: "l"(p), "r"(v), "r"((uint32_t)c) : "memory");
}
__device__ __forceinline__ void st_rlx64_if(bool c, uint32_t* p, uint32_t a, uint32_t b) {
    asm volatile("{\n.reg .pred p;\nsetp.ne.u32 p, %3, 0;\n@p st.relaxed.gpu.global.v2.u32 [%0], {%1,%2};\n}"
                 :: "l"(p), "r"(a), "r"(b), "r"((uint32_t)c) : "memory");
}

__device__ __forceinline__ void st_rlx128_if(bool c, uint32_t* p, uint32_t a, uint32_t b, uint32_t d, uint32_t e) {
    asm volatile("{\n.reg .pred p;\nsetp.ne.u32 p, %5, 0;\n@p st.relaxed.gpu.global.v4.u32 [%0], {%1,%2,%3,%4};\n}"
                 :: "l"(p), "r"(a), "r"(b), "r"(d), "r"(e), "r"((uint32_t)c) : "memory");
}
__device__ __forceinline__ float bf_lo(uint32_t w) { return __uint_as_float(w << 16); }
__device__ __forceinline__ float bf_hi(uint32_t w) { return __uint_as_float(w & 0xffff0000u); }
__device__ __forceinline__ uint32_t pack_bf(float lo, float hi) {
    __nv_bfloat162 v = __floats2bfloat162_rn(lo, hi);
    return *reinterpret_cast<uint32_t*>(&v);
}
__device__ __forceinline__ float rbf(float x) { return __uint_as_float(pack_bf(0.f, x)); }
__device__ __forceinline__ uint32_t enc(uint32_t w) { return w == 0xffffffffu ? 0x80008000u : ~w; }
__device__ __forceinline__ uint4 dec4(const uint4& v) { return make_uint4(~v.x, ~v.y, ~v.z, ~v.w); }

__device__ __forceinline__ float warp_sum(float v) {
#pragma unroll
    for (int o = 16; o > 0; o >>= 1) v += __shfl_xor_sync(0xffffffffu, v, o);
    return v;
}

__device__ __forceinline__ void layernorm_row(const uint4& r0, const uint4& r1, int lane, uint32_t dst_row) {
    const bool act = lane < 28;
    float v[16];
    const uint32_t w[8] = {r0.x, r0.y, r0.z, r0.w, r1.x, r1.y, r1.z, r1.w};
#pragma unroll
    for (int i = 0; i < 8; i++) { v[2 * i] = act ? bf_lo(w[i]) : 0.f; v[2 * i + 1] = act ? bf_hi(w[i]) : 0.f; }
    float s = 0.f;
#pragma unroll
    for (int i = 0; i < 16; i++) s += v[i];
    const float mean = warp_sum(s) * (1.0f / DM);
    float q = 0.f;
#pragma unroll
    for (int i = 0; i < 16; i++) { const float d = v[i] - mean; q = fmaf(d, d, q); }
    const float var = warp_sum(act ? q : 0.f) * (1.0f / DM);
    const float mb = rbf(mean);
    const float sd = rbf(sqrtf(rbf(rbf(var) + 1e-5f)));
    const float rs = 1.0f / sd;
    uint32_t o[8];
#pragma unroll
    for (int i = 0; i < 8; i++) o[i] = pack_bf(rbf(v[2 * i] - mb) * rs, rbf(v[2 * i + 1] - mb) * rs);
    if (act) {
        asm volatile("st.shared.v4.u32 [%0], {%1,%2,%3,%4};" :: "r"(dst_row + lane * 16), "r"(o[0]), "r"(o[1]), "r"(o[2]), "r"(o[3]) : "memory");
        asm volatile("st.shared.v4.u32 [%0], {%1,%2,%3,%4};" :: "r"(dst_row + 448 + lane * 16), "r"(o[4]), "r"(o[5]), "r"(o[6]), "r"(o[7]) : "memory");
    }
}

template <class T> __device__ __forceinline__ T* pin(T* p) { asm volatile("" : "+l"(p)); return p; }
__device__ __forceinline__ uint32_t pin(uint32_t v) { asm volatile("" : "+r"(v)); return v; }
__device__ __forceinline__ void sts32(uint32_t a, float v) { asm volatile("st.shared.f32 [%0], %1;" :: "r"(a), "f"(v) : "memory"); }
__device__ __forceinline__ void sts64(uint32_t a, float x, float y) {
    asm volatile("st.shared.v2.f32 [%0], {%1,%2};" :: "r"(a), "f"(x), "f"(y) : "memory");
}
__device__ __forceinline__ void sts128(uint32_t a, float x, float y, float z, float w) {
    asm volatile("st.shared.v4.f32 [%0], {%1,%2,%3,%4};" :: "r"(a), "f"(x), "f"(y), "f"(z), "f"(w) : "memory");
}
__device__ __forceinline__ float lds32f(uint32_t a) {
    float v;
    asm volatile("ld.shared.f32 %0, [%1];" : "=f"(v) : "r"(a) : "memory");
    return v;
}
__device__ __forceinline__ float2 lds64f(uint32_t a) {
    float2 v;
    asm volatile("ld.shared.v2.f32 {%0,%1}, [%2];" : "=f"(v.x), "=f"(v.y) : "r"(a) : "memory");
    return v;
}
__device__ __forceinline__ float4 lds128f(uint32_t a) {
    float4 v;
    asm volatile("ld.shared.v4.f32 {%0,%1,%2,%3}, [%4];" : "=f"(v.x), "=f"(v.y), "=f"(v.z), "=f"(v.w) : "r"(a) : "memory");
    return v;
}
__device__ __forceinline__ uint32_t add_bf2(uint32_t a, uint32_t b) {
    uint32_t d;
    asm("add.rn.bf16x2 %0, %1, %2;" : "=r"(d) : "r"(a), "r"(b));
    return d;
}
__device__ __forceinline__ uint32_t neg_sq_relu_bf2(uint32_t a) {
    uint32_t d;
    asm("{\n.reg .b32 r, n;\nmax.bf16x2 r, %1, %2;\nneg.bf16x2 n, r;\nmul.rn.bf16x2 %0, r, n;\n}" : "=r"(d) : "r"(a), "r"(0));
    return d;
}

#define V4(v) "+r"(v.x), "+r"(v.y), "+r"(v.z), "+r"(v.w)
#define POLL_TAIL(label) \
    "vote.sync.any.pred q, q, 0xffffffff;\nadd.u32 it, it, 1;\nsetp.lt.and.u32 q, it, 4194304, q;\n@!q bra " label "_END;\n"
__device__ __forceinline__ void poll_nz(uint4& v, const uint32_t* p) {
    asm volatile("{\n.reg .pred p0, q;\n.reg .b32 t, it;\nmov.u32 it, 0;\n"
                 "PA:\nmin.u32 t, %0, %1;\nmin.u32 t, t, %2;\nmin.u32 t, t, %3;\nsetp.eq.u32 p0, t, 0;\nmov.pred q, p0;\n"
                 POLL_TAIL("PA")
                 "@p0 ld.relaxed.gpu.global.v4.u32 {%0,%1,%2,%3}, [%4];\nbra PA;\nPA_END:\n}"
                 : V4(v) : "l"(p) : "memory");
}
__device__ __forceinline__ void poll_nz2(uint4& v, uint4& w, const uint32_t* p) {
    asm volatile("{\n.reg .pred p0, p1, q;\n.reg .b32 t, u, it;\nmov.u32 it, 0;\n"
                 "PB:\nmin.u32 t, %0, %1;\nmin.u32 t, t, %2;\nmin.u32 t, t, %3;\nsetp.eq.u32 p0, t, 0;\n"
                 "min.u32 u, %4, %5;\nmin.u32 u, u, %6;\nmin.u32 u, u, %7;\nsetp.eq.u32 p1, u, 0;\nor.pred q, p0, p1;\n"
                 POLL_TAIL("PB")
                 "@p0 ld.relaxed.gpu.global.v4.u32 {%0,%1,%2,%3}, [%8];\n"
                 "@p1 ld.relaxed.gpu.global.v4.u32 {%4,%5,%6,%7}, [%8+512];\nbra PB;\nPB_END:\n}"
                 : V4(v), V4(w) : "l"(p) : "memory");
}
template <int STRIDE, uint32_t MASK>
__device__ __forceinline__ void poll_bit4(uint4& a, uint4& b, uint4& c, uint4& d, const uint32_t* p, uint32_t want) {
    asm volatile("{\n.reg .pred p0, p1, p2, p3, q;\n.reg .b32 t0, t1, t2, t3, u, it;\nmov.u32 it, 0;\n"
                 "PC:\n"
                 "lop3.b32 t0, %0, %1, %17, 0x7e;\nlop3.b32 u, %2, %3, %17, 0x7e;\nlop3.b32 t0, t0, u, %21, 0xa8;\n"
                 "lop3.b32 t1, %4, %5, %17, 0x7e;\nlop3.b32 u, %6, %7, %17, 0x7e;\nlop3.b32 t1, t1, u, %21, 0xa8;\n"
                 "lop3.b32 t2, %8, %9, %17, 0x7e;\nlop3.b32 u, %10, %11, %17, 0x7e;\nlop3.b32 t2, t2, u, %21, 0xa8;\n"
                 "lop3.b32 t3, %12, %13, %17, 0x7e;\nlop3.b32 u, %14, %15, %17, 0x7e;\nlop3.b32 t3, t3, u, %21, 0xa8;\n"
                 "setp.ne.u32 p0, t0, 0;\nsetp.ne.u32 p1, t1, 0;\nsetp.ne.u32 p2, t2, 0;\nsetp.ne.u32 p3, t3, 0;\n"
                 "or.pred q, p0, p1;\nor.pred q, q, p2;\nor.pred q, q, p3;\n"
                 POLL_TAIL("PC")
                 "@p0 ld.relaxed.gpu.global.v4.u32 {%0,%1,%2,%3}, [%16];\n"
                 "@p1 ld.relaxed.gpu.global.v4.u32 {%4,%5,%6,%7}, [%16+%18];\n"
                 "@p2 ld.relaxed.gpu.global.v4.u32 {%8,%9,%10,%11}, [%16+%19];\n"
                 "@p3 ld.relaxed.gpu.global.v4.u32 {%12,%13,%14,%15}, [%16+%20];\nbra PC;\nPC_END:\n}"
                 : V4(a), V4(b), V4(c), V4(d)
                 : "l"(p), "r"(want), "n"(STRIDE), "n"(2 * STRIDE), "n"(3 * STRIDE), "n"(MASK) : "memory");
}

__device__ __forceinline__ void load_x_pair(const __nv_bfloat16* x, int hd, int j, int lane, uint32_t& x0, uint32_t& x1) {
    const __nv_bfloat16* p = x + (hd >> 1) * DM + j * 64 + (hd & 1) * 32 + (lane & 1) * 16 + ((lane & 7) >> 1) * 2;
    x0 = ldg32_now(p);
    x1 = ldg32_now(p + 8);
}
__device__ __forceinline__ const uint32_t* p2_src(int hd, int j, int lane) {
    return g_p2 + ((j * 16 + hd) * 16 + (lane >> 3)) * 32 + (lane & 7) * 4;
}
__device__ __forceinline__ uint32_t* h_dst(uint32_t par, int hd, int j, int lane) {
    return &g_h[par][(lane >> 3) % HREP][(j * 2 + (hd & 1)) * 128 + (hd >> 1) * 16 + (lane & 7) * 2];
}
#define REDUCE_P2(src, dst, tag, x0, x1) do { \
    const uint32_t* src_ = (src); uint32_t* dst_ = (dst); \
    const uint32_t iv = (tag) ^ 1; \
    uint4 v0 = make_uint4(iv, iv, iv, iv), v1 = v0, v2 = v0, v3 = v0; \
    poll_bit4<512, 1u>(v0, v1, v2, v3, src_, tag); \
    CK32(4); \
    float a0 = (__uint_as_float(v0.x) + __uint_as_float(v1.x)) + (__uint_as_float(v2.x) + __uint_as_float(v3.x)); \
    float a1 = (__uint_as_float(v0.y) + __uint_as_float(v1.y)) + (__uint_as_float(v2.y) + __uint_as_float(v3.y)); \
    float a2 = (__uint_as_float(v0.z) + __uint_as_float(v1.z)) + (__uint_as_float(v2.z) + __uint_as_float(v3.z)); \
    float a3 = (__uint_as_float(v0.w) + __uint_as_float(v1.w)) + (__uint_as_float(v2.w) + __uint_as_float(v3.w)); \
    _Pragma("unroll") \
    for (int o = 8; o <= 16; o <<= 1) { \
        a0 += __shfl_xor_sync(0xffffffffu, a0, o); \
        a1 += __shfl_xor_sync(0xffffffffu, a1, o); \
        a2 += __shfl_xor_sync(0xffffffffu, a2, o); \
        a3 += __shfl_xor_sync(0xffffffffu, a3, o); \
    } \
    st_rlx64_if(lane < 8 * HREP, dst_, enc(add_bf2(x0, pack_bf(a0, a1))), enc(add_bf2(x1, pack_bf(a2, a3)))); \
    CK32(5); \
} while (0)

__global__ void __launch_bounds__(NTHREADS, 1)
fused_decode_kernel(const __nv_bfloat16* __restrict__ x, const __nv_bfloat16* __restrict__ wq,
                    const __nv_bfloat16* __restrict__ wo,
                    const __nv_bfloat16* __restrict__ b1, const __nv_bfloat16* __restrict__ b2,
                    __nv_bfloat16* __restrict__ out,
                    const __grid_constant__ CUtensorMap tm_k, const __grid_constant__ CUtensorMap tm_v,
                    const __grid_constant__ CUtensorMap tm_wo, const __grid_constant__ CUtensorMap tm_w1,
                    const __grid_constant__ CUtensorMap tm_w2) {
    extern __shared__ __align__(1024) uint8_t sp[];
    const uint32_t sb = pin(smem_u32(sp));

    const int tid = threadIdx.x, warp = tid >> 5, lane = tid & 31;
    const int cta = blockIdx.x;
    CKDECL;
    const int hd = cta >> 3, bj = cta & 7;
    const bool tail = bj < 7;
    const int r = hd * 7 + bj;
    const int r1 = R1MAP ? bj * 16 + hd : r;
    const uint32_t bar_full = sb + OFF_BAR, bar_empty = bar_full + NS * 8, bar_w = bar_empty + NS * 8;

    const uint32_t s_wq = sb + OFF_WO, s_est = sb + OFF_M + 192;
    uint4 xr0 = make_uint4(0, 0, 0, 0), xr1 = xr0;
    if (warp < 8) {
        if (lane < 28) {
            xr0 = ldg128_now(x + warp * DM + lane * 8);
            xr1 = ldg128_now(x + warp * DM + 224 + lane * 8);
        }
        const int row = tid >> 2, ch = tid & 3;
        const uint32_t d = s_wq + row * 64 + ((ch ^ ((row >> 1) & 3)) << 4);
        const __nv_bfloat16* p = wq + (size_t)row * (NH * DH) + cta * 32 + ch * 8;
#pragma unroll
        for (int i = 0; i < 7; i++)
            asm volatile("cp.async.cg.shared.global.L2::128B [%0], [%1], 16;"
                         :: "r"(d + i * 4096), "l"(p + (size_t)i * 64 * (NH * DH)) : "memory");
        asm volatile("bar.arrive 7, %0;" :: "n"(NTHREADS) : "memory");
    }
    const int grp0 = (bj * NH + hd) * (SK / 8);
    const int rot = ROT;
    uint64_t pol;
    asm volatile("createpolicy.fractional.L2::evict_first.b64 %0, 1.0;" : "=l"(pol));
    PROF(tid == PROF0, 0);
    if (tid == 256) {
        asm volatile("prefetch.tensormap [%0];" :: "l"(&tm_k) : "memory");
#pragma unroll
        for (int s = 0; s < D0; s++) mbar_init(bar_full + s * 8, 1);
        asm volatile("fence.mbarrier_init.release.cluster;" ::: "memory");
        asm volatile("st.volatile.shared.v2.u32 [%0], {%1,%2};" :: "r"(s_est), "r"(0), "r"(clock32()) : "memory");
    }
    if (warp >= 8) { __syncwarp(); asm volatile("bar.sync 7, %0;" :: "n"(NTHREADS) : "memory"); }
    if (tid == 256) {
        const uint32_t c0 = clock32();
        while (clock32() - c0 < KCYC) {}
#pragma unroll
        for (int s = 0; s < D0; s++) {
            mbar_expect_tx(bar_full + s * 8, STAGE);
            tma_tile(sb + OFF_RING + s * STAGE, &tm_k, grp0 + ((s + rot) & (KT - 1)) * 4, bar_full + s * 8, pol);
        }
    }

    if (warp == 9) {
        uint32_t epoch, v = 0;
        asm volatile("ld.relaxed.gpu.global.u32 %0, [%1];" : "=r"(epoch) : "l"(&g_epoch) : "memory");
        const uint32_t* prog = g_prog[(epoch + 1) & 1];
        const uint32_t* qsrc = &g_q[(epoch + 1) & 1][bj * (NH * DH / 2) + hd * (DH / 2) + lane * 4];
        bool wait_q = true;
#pragma unroll 1
        for (int it = 0; v + WIN < (NT - 1 - SPRINT) * NCTA && it < SPIN_MAX; it++) {
            asm volatile("ld.relaxed.gpu.global.u32 %0, [%1];" : "=r"(v) : "l"(prog) : "memory");
            if (wait_q) {
                const uint4 q = ld_rlx128(qsrc);
                if (it == SPIN_MAX / 2 || __all_sync(0xffffffffu, min(min(q.x, q.y), min(q.z, q.w)) != 0)) {
                    *reinterpret_cast<uint4*>(sp + OFF_Q + lane * 16) = dec4(q);
                    asm volatile("bar.arrive 5, 288;" ::: "memory");
                    wait_q = false;
                }
            }
            if (lane == 0) asm volatile("st.volatile.shared.v2.u32 [%0], {%1,%2};" :: "r"(s_est), "r"(v), "r"(clock32()) : "memory");
            if (!wait_q) __nanosleep(HSLEEP);
        }
        return;
    }
    if (warp == 8) {
        if (lane == 0) {
#pragma unroll
            for (int s = D0; s < NS; s++) mbar_init(bar_full + s * 8, 1);
#pragma unroll
            for (int s = 0; s < NS; s++) mbar_init(bar_empty + s * 8, 8);
#pragma unroll
            for (int s = 0; s < 4; s++) mbar_init(bar_w + s * 8, 1);
            asm volatile("fence.mbarrier_init.release.cluster;" ::: "memory");
        }
        __syncwarp();
        asm volatile("bar.arrive 3, 288;" ::: "memory");
        uint32_t epoch;
        asm volatile("ld.relaxed.gpu.global.u32 %0, [%1];" : "=r"(epoch) : "l"(&g_epoch) : "memory");
        uint32_t x0 = 0, x1 = 0;
        if (!REDNT && tail) load_x_pair(x, hd, bj, lane, x0, x1);
        if (lane == 0) {
            asm volatile("prefetch.tensormap [%0];" :: "l"(&tm_v) : "memory");
            asm volatile("prefetch.tensormap [%0];" :: "l"(&tm_wo) : "memory");
            asm volatile("prefetch.tensormap [%0];" :: "l"(&tm_w1) : "memory");
            asm volatile("prefetch.tensormap [%0];" :: "l"(&tm_w2) : "memory");
            uint32_t* prog = g_prog[(epoch + 1) & 1];
            uint32_t t = D0, landed = 0;
#pragma unroll 1
            for (int it = 0; t < NT && it < 16 * SPIN_MAX; it++) {
                if (landed < t && mbar_test(bar_full + (landed & (NS - 1)) * 8, (landed / NS) & 1)) {
                    landed++;
                    if (((landed + cta) & 3) == 0) asm volatile("red.relaxed.gpu.global.add.u32 [%0], 4;" :: "l"(prog) : "memory");
                }
                if (t - landed >= NS) continue;
                if (t - landed >= MINF && t < NT - SPRINT) {
                    uint32_t v, c0;
                    asm volatile("ld.volatile.shared.v2.u32 {%0,%1}, [%2];" : "=r"(v), "=r"(c0) : "r"(s_est) : "memory");
                    if (t * NCTA > v + min(((clock32() - c0) * 7) >> 6, 256u) + WIN) continue;
                }
                const uint32_t s = t & (NS - 1);
                if (t >= NS && !mbar_test(bar_empty + s * 8, (t / NS - 1) & 1)) continue;
                mbar_expect_tx(bar_full + s * 8, STAGE);
                tma_tile(sb + OFF_RING + s * STAGE, t < KT ? &tm_k : &tm_v, grp0 + ((t + rot) & (KT - 1)) * 4, bar_full + s * 8, pol);
                if (PFO_T >= 0 && t == PFO_T)
                    asm volatile("cp.async.bulk.prefetch.L2.global [%0], %1;" :: "l"(wo + (size_t)cta * (32 * DM)), "r"(32 * DM * 2) : "memory");
                if (tail) {
                    if (t == WOA_T) {
                        mbar_expect_tx(bar_w, 128 * 128);
                        tma_2d(sb + OFF_WO, &tm_wo, bj * 64, hd * DH, bar_w);
                    }
                    if (t == WOB_T) {
                        mbar_expect_tx(bar_w + 24, 128 * 128);
                        tma_2d(sb + OFF_WO + 128 * 128, &tm_wo, bj * 64, hd * DH + 128, bar_w + 24);
                    }
                    if (!W1LATE && X1 < 0) {
                        if (t == W1_T0) mbar_expect_tx(bar_w + 8, DM * 32);
#pragma unroll
                        for (int i = 0; i < 2; i++)
                            if (t == W1_T0 + i * W1_STEP) tma_2d(sb + OFF_W1 + i * 224 * 32, &tm_w1, r1 * 16, i * 224, bar_w + 8);
                    }
                    if (t == W2_T0) mbar_expect_tx(bar_w + 16, FF * 16);
#pragma unroll
                    for (int i = 0; i < 7; i++)
                        if (t == W2_T0 + i * W2_STEP) tma_2d(sb + OFF_W2 + i * 4096, &tm_w2, (r >> 1) * 8, i * 256, bar_w + 16);
                }
                t++;
            }
            asm volatile("red.relaxed.gpu.global.add.u32 [%0], %1;" :: "l"(prog), "r"(NT - ((landed + (cta & 3)) & ~3u)) : "memory");
            if (X1 >= 0 && tail) {
                mbar_wait(bar_full + ((NT - 1 - X1) & (NS - 1)) * 8, ((NT - 1 - X1) / NS) & 1);
                mbar_expect_tx(bar_w + 8, DM * 32);
                tma_2d(sb + OFF_W1, &tm_w1, r1 * 16, 0, bar_w + 8);
                tma_2d(sb + OFF_W1 + 224 * 32, &tm_w1, r1 * 16, 224, bar_w + 8);
            }
        }
        __syncwarp();
        if (!REDNT && tail) {
            const uint32_t tag = (epoch + 1) & 1;
            REDUCE_P2(pin(p2_src(hd, bj, lane)), pin(h_dst(tag, hd, bj, lane)), tag, x0, x1);
            CKOUT();
        }
        return;
    }

    const int g = lane >> 2, t4 = lane & 3;
    asm volatile("cp.async.commit_group;" ::: "memory");
    uint32_t epoch;
    asm volatile("ld.relaxed.gpu.global.u32 %0, [%1];" : "=r"(epoch) : "l"(&g_epoch) : "memory");
    epoch += 1;
    const uint32_t par = epoch & 1;
    const int bg = r & 1, cg = r >> 1;
    uint32_t bias1a = 0, bias1b = 0, bias2w = 0;
    if (warp == 7 && tail) {
        bias1a = ldg32_now(b1 + r1 * 16 + t4 * 2);
        bias1b = ldg32_now(b1 + r1 * 16 + 8 + t4 * 2);
        bias2w = ldg32_now(b2 + cg * 8 + (lane & 6)) >> ((lane & 1) * 16);
    }
    if (REDNT && !tail && warp < 7) load_x_pair(x, hd, warp, lane, bias1a, bias1b);

    layernorm_row(xr0, xr1, lane, sb + OFF_C + warp * (XP * 2));
    asm volatile("cp.async.wait_group 0;" ::: "memory");
    asm volatile("bar.sync 3, 288;" ::: "memory");

    float* red_b = reinterpret_cast<float*>(sp + OFF_B);
    if (warp < 7) {
        float acc[4][4] = {};
#pragma unroll
        for (int p = 0; p < 2; p++) {
            const uint4 a = ldm4(sb + OFF_C + (lane & 7) * (XP * 2) + (warp * 64 + p * 32 + (lane >> 3) * 8) * 2);
#pragma unroll
            for (int s = 0; s < 2; s++) {
                const int row = warp * 64 + p * 32 + s * 16 + ((lane >> 3) & 1) * 8 + (lane & 7);
#pragma unroll
                for (int np = 0; np < 2; np++) {
                    const int ch = np * 2 + (lane >> 4);
                    const uint4 bw = ldm4t(s_wq + row * 64 + ((ch ^ ((row >> 1) & 3)) << 4));
                    mma16816(acc[np * 2], s ? a.z : a.x, 0, s ? a.w : a.y, 0, bw.x, bw.y);
                    mma16816(acc[np * 2 + 1], s ? a.z : a.x, 0, s ? a.w : a.y, 0, bw.z, bw.w);
                }
            }
        }
#pragma unroll
        for (int n = 0; n < 4; n++)
            *reinterpret_cast<float2*>(red_b + (warp * 8 + g) * 40 + n * 8 + t4 * 2) = make_float2(acc[n][0], acc[n][1]);
    }
    cbar();
    if (tid < 128) {
        const int b = tid >> 4, wd = tid & 15;
        float s0 = 0.f, s1 = 0.f;
#pragma unroll
        for (int w = 0; w < 7; w++) {
            const float2 p = *reinterpret_cast<const float2*>(red_b + (w * 8 + b) * 40 + wd * 2);
            s0 += p.x; s1 += p.y;
        }
        st_rlx32(&g_q[par][b * (NH * DH / 2) + cta * 16 + (wd & 3) * 4 + ((wd >> 2) & 1) * 2 + (wd >> 3)], enc(pack_bf(s0, s1)));
    } else {
        const int i = tid - 128;
        g_q[par ^ 1][(i >> 4) * (NH * DH / 2) + cta * 16 + (i & 15)] = 0;
        g_o[par ^ 1][cta * 128 + i] = 0;
        if (cta == 0 && i == 0) g_prog[par ^ 1][0] = 0;
        if (tail && i < 64) g_g[par ^ 1][((i >> 5) * NTAIL + r1) * 32 + (i & 31)] = 0;
        if (tail && i < 16 * HREP) g_h[par ^ 1][i >> 4][(bj * 2 + (hd & 1)) * 128 + (hd >> 1) * 16 + (i & 15)] = 0;
    }
    PROF(tid == 0, 1);
    asm volatile("fence.proxy.async.shared::cta;" ::: "memory");

    uint32_t* const p_o_st = pin(&g_o[par][(hd * 8 + warp) * 128 + bj * 16 + t4 * 4]);
    const uint32_t* const p_o_ld = pin(&g_o[par][(hd * 8 + warp) * 128 + lane * 4]);
    uint32_t* const p_p2_st = pin(g_p2 + ((bj * 16 + warp * 2 + (lane >> 4)) * 16 + hd) * 32 + (lane & 15) * 2);
    const uint32_t* const p_h_ld = pin(tail ? &g_h[par][cta % HREP][warp * 256 + lane * 4] : p2_src(hd, warp, lane));
    uint32_t* const p_g_st = pin(tail ? &g_g[par][((g >> 2) * NTAIL + r1) * 32 + (g & 3) * 8 + t4 * 2] : h_dst(par, hd, warp, lane));
    const uint32_t* const p_g_ld =
        pin(&g_g[par][(bg * NTAIL + warp * 16 + (g >> 2) * 8 + (t4 >> 1)) * 32 + (g & 3) * 8 + (t4 & 1) * 4]);
    __nv_bfloat16* const p_out = pin(out + (bg * 4 + (lane >> 3)) * DM + cg * 8 + (lane & 7));
    const uint32_t a_wo = pin(sb + OFF_WO + (warp * 32 + (lane >> 4) * 8 + (lane & 7)) * 128 + ((((lane >> 3) & 1) ^ (lane & 7)) << 4));
    const uint32_t a_w1 = pin(sb + OFF_W1 + (((lane >> 3) & 1) * 8 + (lane & 7)) * 32 + (lane >> 4) * 16);
    const uint32_t a_w2 = pin(sb + OFF_W2 + (warp * 256 + ((lane >> 3) & 1) * 128 + ((lane >> 2) & 1) * 16 + (lane >> 4) * 8 +
                                             ((lane >> 1) & 1) * 4 + (lane & 1)) * 16);
    const uint32_t o_r2w = pin((uint32_t)(((warp * 8 + t4 * 2) * 68 + g) * 4));
    const uint32_t o_r2r = pin((uint32_t)((warp * 68 + (lane >> 4) * 32 + ((lane >> 1) & 1) * 16 + (lane & 1) * 8 + ((lane >> 2) & 3) * 2) * 4));
    const uint32_t a_r4 = pin(sb + OFF_C + lane * 16);
    const uint32_t a_st = pin(sb + OFF_C + 4096 + g * 8);
    const uint32_t a_r5 = pin(sb + OFF_C + 5120 + (warp < 7 ? warp * 128 + ((t4 & 1) * 16 + g) * 4 : lane * 4));
    const uint32_t a_hres = pin(sb + OFF_M + 64 + (warp < 7 ? lane * 4 : (bg * 4 + (lane >> 3)) * 16 + (lane & 7) * 2));
    __nv_bfloat16* sc = reinterpret_cast<__nv_bfloat16*>(sp + OFF_A);

    {
        float oa[4][4] = {}, ob[4][4] = {};
        uint4 ov = make_uint4(0, 0, 0, 0);
        {
            uint4 q[8];
            {
                asm volatile("bar.sync 5, 288;" ::: "memory");
#pragma unroll
                for (int i = 0; i < 8; i++) q[i] = lds128(sb + OFF_Q + i * 64 + t4 * 16);
            }
            PROF(tid == 0, 2);

            float mx = -INFINITY;
            {
                const uint32_t ka = pin(sb + OFF_RING + (warp & 3) * 4096 + (lane & 7) * 128 + (((lane >> 3) ^ (lane & 7)) << 4));
                uint32_t* scw = reinterpret_cast<uint32_t*>(sc) + t4 * 4 + (warp & 1) * 2 + ((warp >> 1) & 1);
#pragma unroll 1
                for (int t = warp >> 2; t < KT; t += 2) {
                    const int st = t & (NS - 1);
                    mbar_wait(bar_full + st * 8, (t / NS) & 1);
                    uint4 kf[8];
#pragma unroll
                    for (int i = 0; i < 8; i++) kf[i] = ldm4((ka ^ ((i & 1) << 6)) + st * STAGE + (i >> 1) * 1024);
                    float c[4][4] = {};
#pragma unroll
                    for (int i = 0; i < 8; i++) {
                        mma16816(c[(i & 1) * 2], q[i].x, q[i].y, q[i].z, q[i].w, kf[i].x, kf[i].y);
                        mma16816(c[(i & 1) * 2 + 1], q[i].x, q[i].y, q[i].z, q[i].w, kf[i].z, kf[i].w);
                    }
                    if (lane == 0) mbar_arrive2(bar_empty + st * 8);
                    const uint32_t d = pack_bf((c[0][0] + c[2][0]) + (c[1][2] + c[3][2]), (c[0][1] + c[2][1]) + (c[1][3] + c[3][3]));
                    const uint32_t sw = pack_bf(bf_lo(d) * 0.0625f, bf_hi(d) * 0.0625f);
                    mx = fmaxf(mx, fmaxf(bf_lo(sw), bf_hi(sw)));
                    if (lane < 4) scw[t * 16] = sw;
                }
            }
            PROF(tid == 0, 3);

            float* sm_m = reinterpret_cast<float*>(sp + OFF_M);
            mx = fmaxf(mx, __shfl_xor_sync(0xffffffffu, mx, 1));
            mx = fmaxf(mx, __shfl_xor_sync(0xffffffffu, mx, 2));
            if (lane == 0) sm_m[warp] = mx;
            cbar();
#pragma unroll
            for (int w = 0; w < 8; w++) mx = fmaxf(mx, sm_m[w]);
            {
                float e[16], sum = 0.f;
#pragma unroll
                for (int i = 0; i < 4; i++) {
                    const uint2 s = *reinterpret_cast<const uint2*>(sc + i * 1024 + tid * 4);
                    e[i * 4 + 0] = expf(bf_lo(s.x) - mx); e[i * 4 + 1] = expf(bf_hi(s.x) - mx);
                    e[i * 4 + 2] = expf(bf_lo(s.y) - mx); e[i * 4 + 3] = expf(bf_hi(s.y) - mx);
                    sum += (e[i * 4] + e[i * 4 + 1]) + (e[i * 4 + 2] + e[i * 4 + 3]);
                }
                sum = warp_sum(sum);
                if (lane == 0) sm_m[8 + warp] = sum;
                cbar();
                sum = 0.f;
#pragma unroll
                for (int w = 0; w < 8; w++) sum += sm_m[8 + w];
                const float inv = 1.0f / sum;
#pragma unroll
                for (int i = 0; i < 4; i++)
                    *reinterpret_cast<uint2*>(sc + i * 1024 + tid * 4) =
                        make_uint2(pack_bf(e[i * 4] * inv, e[i * 4 + 1] * inv), pack_bf(e[i * 4 + 2] * inv, e[i * 4 + 3] * inv));
                cbar();
            }
            CK32(11);
            PROF(tid == 0, 4);

            const uint32_t va = pin(sb + OFF_RING + ((lane >> 3) & 1) * 4096 + (warp >> 1) * 1024 + (lane & 7) * 128 +
                                    ((((warp & 1) * 4 + (lane >> 4)) ^ (lane & 7)) << 4));
            auto pv_tile = [&](int t) {
                const int st = t & (NS - 1);
                const uint4 p = lds128(sb + OFF_A + t * 64 + t4 * 16);
                const uint32_t va0 = pin(va + st * STAGE), va1 = pin(va0 ^ 32);
                mbar_wait(bar_full + st * 8, ((KT + t) / NS) & 1);
                const uint4 v0 = ldm4t(va0), v1 = ldm4t(va1), v2 = ldm4t(va0 + 8192), v3 = ldm4t(va1 + 8192);
                mma16816(oa[0], p.x, p.y, p.z, p.w, v0.x, v0.y);
                mma16816(oa[1], p.x, p.y, p.z, p.w, v0.z, v0.w);
                mma16816(oa[2], p.x, p.y, p.z, p.w, v1.x, v1.y);
                mma16816(oa[3], p.x, p.y, p.z, p.w, v1.z, v1.w);
                mma16816(ob[0], p.x, p.y, p.z, p.w, v2.x, v2.y);
                mma16816(ob[1], p.x, p.y, p.z, p.w, v2.z, v2.w);
                mma16816(ob[2], p.x, p.y, p.z, p.w, v3.x, v3.y);
                mma16816(ob[3], p.x, p.y, p.z, p.w, v3.z, v3.w);
                if (lane == 0) mbar_arrive(bar_empty + st * 8);
            };
#pragma unroll 1
            for (int t = 0; t < KT - OEARLY; t++) pv_tile(t);
            if (OEARLY) ld_rlx128_if(tail, ov, p_o_ld);
#pragma unroll 1
            for (int t = KT - OEARLY; t < KT; t++) pv_tile(t);
            CK32(0);
        }

        st_rlx128_if(lane < 4, p_o_st,
                     enc(pack_bf(oa[0][0] + ob[0][2], oa[0][1] + ob[0][3])), enc(pack_bf(oa[1][0] + ob[1][2], oa[1][1] + ob[1][3])),
                     enc(pack_bf(oa[2][0] + ob[2][2], oa[2][1] + ob[2][3])), enc(pack_bf(oa[3][0] + ob[3][2], oa[3][1] + ob[3][3])));
        CK32(1);
        if (!tail) {
            if (REDNT && warp < 7) REDUCE_P2(p_h_ld, p_g_st, par, bias1a, bias1b);
            CKOUT();
            return;
        }

        {
            const uint32_t red_a = sb + OFF_RING + ((NT - 3) % NS) * STAGE;
            uint4 v = ov;
            ld_rlx128_if(min(min(v.x, v.y), min(v.z, v.w)) == 0, v, p_o_ld);
            mbar_wait(bar_w + (warp >> 2) * 24, 0);
            mbar_wait(bar_empty + ((NT - 3) % NS) * 8, ((NT - 3) / NS) & 1);
            mbar_wait(bar_empty + ((NT - 2) % NS) * 8, ((NT - 2) / NS) & 1);
            uint4 a[2][4];
#pragma unroll
            for (int s = 0; s < 2; s++)
#pragma unroll
                for (int mt = 0; mt < 4; mt++) a[s][mt] = ldm4t((a_wo ^ (mt << 5)) + s * 2048);
            poll_nz(v, p_o_ld);
            CK32(2);
            v = dec4(v);
            float acc[4][4] = {};
#pragma unroll
            for (int mt = 0; mt < 4; mt++) mma16816(acc[mt], a[0][mt].x, a[0][mt].y, a[0][mt].z, a[0][mt].w, v.x, v.y);
#pragma unroll
            for (int mt = 0; mt < 4; mt++) mma16816(acc[mt], a[1][mt].x, a[1][mt].y, a[1][mt].z, a[1][mt].w, v.z, v.w);
#pragma unroll
            for (int mt = 0; mt < 4; mt++) {
                sts32(red_a + o_r2w + mt * 64, acc[mt][0]);
                sts32(red_a + o_r2w + mt * 64 + 272, acc[mt][1]);
                sts32(red_a + o_r2w + mt * 64 + 32, acc[mt][2]);
                sts32(red_a + o_r2w + mt * 64 + 304, acc[mt][3]);
            }
            cbar();
            float2 p[8];
#pragma unroll
            for (int w = 0; w < 8; w++) p[w] = lds64f(red_a + o_r2r + w * (8 * 272));
            const float s0 = ((p[0].x + p[1].x) + (p[2].x + p[3].x)) + ((p[4].x + p[5].x) + (p[6].x + p[7].x));
            const float s1 = ((p[0].y + p[1].y) + (p[2].y + p[3].y)) + ((p[4].y + p[5].y) + (p[6].y + p[7].y));
            st_rlx64(p_p2_st, (__float_as_uint(s0) & ~1u) | par, (__float_as_uint(s1) & ~1u) | par);
        }
        CK32(3);

        constexpr uint32_t ONES = 0x3f803f80u;
        if (warp < 7) {
            uint4 v0 = ld_rlx128(p_h_ld), v1 = ld_rlx128(p_h_ld + 128);
            mbar_wait(bar_w + 16, 0);
            uint4 aw[8];
#pragma unroll
            for (int s = 0; s < 8; s++) aw[s] = ldm4t(a_w2 + (s >> 1) * 512 + (s & 1) * 32);
            mbar_wait(bar_w + 8, 0);
            uint4 bw[4];
#pragma unroll
            for (int s = 0; s < 4; s++) bw[s] = ldm4t(a_w1 + warp * 2048 + s * 512);
            poll_nz2(v0, v1, p_h_ld);
            CK32(6);
            v0 = dec4(v0); v1 = dec4(v1);
            const uint32_t hw[8] = {v0.x, v0.y, v0.z, v0.w, v1.x, v1.y, v1.z, v1.w};
            float c0[4] = {}, c1[4] = {}, cs[4] = {};
#pragma unroll
            for (int s = 0; s < 4; s++) {
                mma16816(cs, hw[2 * s], ONES, hw[2 * s + 1], ONES, hw[2 * s], hw[2 * s + 1]);
                mma16816(c0, hw[2 * s], ONES, hw[2 * s + 1], ONES, bw[s].x, bw[s].y);
                mma16816(c1, hw[2 * s], ONES, hw[2 * s + 1], ONES, bw[s].z, bw[s].w);
            }
            if (warp == (cg >> 3)) {
                const uint4 hv = (cg & 4) ? v1 : v0;
                const uint32_t hx = (cg & 2) ? ((cg & 1) ? hv.w : hv.z) : ((cg & 1) ? hv.y : hv.x);
                sts32(a_hres, __uint_as_float(hx));
            }
            if (t4 == (g >> 1)) sts64(a_st + warp * 64, (g & 1) ? cs[3] : cs[2], (g & 1) ? cs[1] : cs[0]);
            sts128(a_r4 + warp * 512, c0[0], c0[1], c1[0], c1[1]);
            asm volatile("bar.arrive 2, 256;" ::: "memory");
            CK32(7);

            if (GATE_G) asm volatile("bar.sync 6, 256;" ::: "memory");
            uint4 u0 = ld_rlx128(p_g_ld), u1 = ld_rlx128(p_g_ld + 64), u2 = ld_rlx128(p_g_ld + 128), u3 = ld_rlx128(p_g_ld + 192);
            poll_bit4<256, 0x80000000u>(u0, u1, u2, u3, p_g_ld, 0x80000000u);
            CK32(9);
            float y0[4] = {}, y1[4] = {}, y2[4] = {}, y3[4] = {};
            mma16816(y0, aw[0].x, aw[0].y, aw[0].z, aw[0].w, u0.x, u0.y);
            mma16816(y1, aw[2].x, aw[2].y, aw[2].z, aw[2].w, u1.x, u1.y);
            mma16816(y2, aw[4].x, aw[4].y, aw[4].z, aw[4].w, u2.x, u2.y);
            mma16816(y3, aw[6].x, aw[6].y, aw[6].z, aw[6].w, u3.x, u3.y);
            mma16816(y0, aw[1].x, aw[1].y, aw[1].z, aw[1].w, u0.z, u0.w);
            mma16816(y1, aw[3].x, aw[3].y, aw[3].z, aw[3].w, u1.z, u1.w);
            mma16816(y2, aw[5].x, aw[5].y, aw[5].z, aw[5].w, u2.z, u2.w);
            mma16816(y3, aw[7].x, aw[7].y, aw[7].z, aw[7].w, u3.z, u3.w);
            const bool lo = t4 < 2;
            const float z0 = ((lo ? y0[0] : y0[2]) + (lo ? y1[0] : y1[2])) + ((lo ? y2[0] : y2[2]) + (lo ? y3[0] : y3[2]));
            const float z1 = ((lo ? y0[1] : y0[3]) + (lo ? y1[1] : y1[3])) + ((lo ? y2[1] : y2[3]) + (lo ? y3[1] : y3[3]));
            sts32(a_r5 + (lo ? 0 : 896), z0);
            sts32(a_r5 + (lo ? 32 : 928), z1);
            asm volatile("bar.arrive 4, 256;" ::: "memory");
        } else {
            float w0[4] = {}, w1s[4] = {}, w2s[4] = {}, w3s[4] = {};
            if (W1LATE && lane == 0) {
                mbar_expect_tx(bar_w + 8, DM * 32);
                tma_2d(sb + OFF_W1, &tm_w1, r1 * 16, 0, bar_w + 8);
                tma_2d(sb + OFF_W1 + 224 * 32, &tm_w1, r1 * 16, 224, bar_w + 8);
            }
            __syncwarp();
            mbar_wait(bar_w + 8, 0);
#pragma unroll 1
            for (int s = 0; s < 28; s += 14) {
                uint4 bw[14];
#pragma unroll
                for (int i = 0; i < 14; i++) bw[i] = ldm4t(a_w1 + (s + i) * 512);
#pragma unroll
                for (int i = 0; i < 14; i += 2) {
                    mma16816(w0, ONES, ONES, ONES, ONES, bw[i].x, bw[i].y);
                    mma16816(w1s, ONES, ONES, ONES, ONES, bw[i].z, bw[i].w);
                    mma16816(w2s, ONES, ONES, ONES, ONES, bw[i + 1].x, bw[i + 1].y);
                    mma16816(w3s, ONES, ONES, ONES, ONES, bw[i + 1].z, bw[i + 1].w);
                }
            }
            w0[0] += w2s[0]; w0[1] += w2s[1]; w1s[0] += w3s[0]; w1s[1] += w3s[1];
            asm volatile("bar.sync 2, 256;" ::: "memory");
            float2 sq[7];
            float4 p[7];
#pragma unroll
            for (int w = 0; w < 7; w++) sq[w] = lds64f(a_st + w * 64);
#pragma unroll
            for (int w = 0; w < 7; w++) p[w] = lds128f(a_r4 + w * 512);
            const float mean = (((sq[0].x + sq[1].x) + (sq[2].x + sq[3].x)) + ((sq[4].x + sq[5].x) + sq[6].x)) * (1.0f / DM);
            const float msq = (((sq[0].y + sq[1].y) + (sq[2].y + sq[3].y)) + ((sq[4].y + sq[5].y) + sq[6].y)) * (1.0f / DM);
            const float var = fmaxf(fmaf(-mean, mean, msq), 0.f);
            float sd, rs;
            asm("sqrt.approx.ftz.f32 %0, %1;" : "=f"(sd) : "f"(rbf(rbf(var) + 1e-5f)));
            asm("rcp.approx.ftz.f32 %0, %1;" : "=f"(rs) : "f"(rbf(sd)));
            const float mb = rbf(mean);
            const float s0 = fmaf(-mb, w0[0], ((p[0].x + p[1].x) + (p[2].x + p[3].x)) + ((p[4].x + p[5].x) + p[6].x));
            const float s1 = fmaf(-mb, w0[1], ((p[0].y + p[1].y) + (p[2].y + p[3].y)) + ((p[4].y + p[5].y) + p[6].y));
            const float s2 = fmaf(-mb, w1s[0], ((p[0].z + p[1].z) + (p[2].z + p[3].z)) + ((p[4].z + p[5].z) + p[6].z));
            const float s3 = fmaf(-mb, w1s[1], ((p[0].w + p[1].w) + (p[2].w + p[3].w)) + ((p[4].w + p[5].w) + p[6].w));
            st_rlx64(p_g_st, neg_sq_relu_bf2(add_bf2(pack_bf(s0 * rs, s1 * rs), bias1a)),
                        neg_sq_relu_bf2(add_bf2(pack_bf(s2 * rs, s3 * rs), bias1b)));
            if (GATE_G) asm volatile("bar.arrive 6, 256;" ::: "memory");
            CK32(8);
            uint16_t hraw;
            asm volatile("ld.shared.u16 %0, [%1];" : "=h"(hraw) : "r"(a_hres) : "memory");
            asm volatile("bar.sync 4, 256;" ::: "memory");
            float y[14];
#pragma unroll
            for (int w = 0; w < 14; w++) y[w] = lds32f(a_r5 + w * 128);
            const float ys = (((y[0] + y[1]) + (y[2] + y[3])) + ((y[4] + y[5]) + (y[6] + y[7]))) +
                             (((y[8] + y[9]) + (y[10] + y[11])) + (y[12] + y[13]));
            const uint32_t res = add_bf2(hraw, add_bf2(pack_bf(-ys, 0.f), bias2w));
            asm volatile("st.global.u16 [%0], %1;" :: "l"(p_out), "h"((uint16_t)res) : "memory");
            if (cta == 0 && lane == 0) st_rlx32(&g_epoch, epoch);
            CK32(10);
        }
        CKOUT();
    }
}

typedef CUresult (*EncodeTiledFn)(CUtensorMap*, CUtensorMapDataType, cuuint32_t, void*, const cuuint64_t*,
                                  const cuuint64_t*, const cuuint32_t*, const cuuint32_t*, CUtensorMapInterleave,
                                  CUtensorMapSwizzle, CUtensorMapL2promotion, CUtensorMapFloatOOBfill);

void encode_2d(EncodeTiledFn fn, CUtensorMap* tm, void* base, int rows, int cols, int box_rows, int box_cols,
               CUtensorMapSwizzle sw) {
    cuuint64_t dims[2] = {(cuuint64_t)cols, (cuuint64_t)rows};
    cuuint64_t strides[1] = {(cuuint64_t)cols * 2};
    cuuint32_t box[2] = {(cuuint32_t)box_cols, (cuuint32_t)box_rows};
    cuuint32_t es[2] = {1, 1};
    fn(tm, CU_TENSOR_MAP_DATA_TYPE_BFLOAT16, 2, base, dims, strides, box, es, CU_TENSOR_MAP_INTERLEAVE_NONE, sw,
       CU_TENSOR_MAP_L2_PROMOTION_L2_128B, CU_TENSOR_MAP_FLOAT_OOB_FILL_NONE);
}

void encode_kv(EncodeTiledFn fn, CUtensorMap* tm, void* base) {
    cuuint64_t dims[4] = {64, 8, 4, (cuuint64_t)NB * NH * SK / 8};
    cuuint64_t strides[3] = {DH * 2, 128, 8 * DH * 2};
    cuuint32_t box[4] = {64, 8, 4, TILE_KEYS / 8};
    cuuint32_t es[4] = {1, 1, 1, 1};
    fn(tm, CU_TENSOR_MAP_DATA_TYPE_BFLOAT16, 4, base, dims, strides, box, es, CU_TENSOR_MAP_INTERLEAVE_NONE,
       CU_TENSOR_MAP_SWIZZLE_128B, CU_TENSOR_MAP_L2_PROMOTION_NONE, CU_TENSOR_MAP_FLOAT_OOB_FILL_NONE);
}

}

extern "C" void kernel_launch(void* const* d_in, const int* in_sizes, int n_in, void* d_out, int out_size) {
    (void)in_sizes; (void)n_in; (void)out_size;
    static EncodeTiledFn encode = nullptr;
    if (!encode) {
        void* fn = nullptr;
        cudaDriverEntryPointQueryResult qr;
        cudaGetDriverEntryPoint("cuTensorMapEncodeTiled", &fn, cudaEnableDefault, &qr);
        encode = (EncodeTiledFn)fn;
        cudaFuncSetAttribute(fused_decode_kernel, cudaFuncAttributeMaxDynamicSharedMemorySize, SMEM_BYTES);
    }
    CUtensorMap tm_k, tm_v, tm_wo, tm_w1, tm_w2;
    encode_kv(encode, &tm_k, d_in[1]);
    encode_kv(encode, &tm_v, d_in[2]);
    encode_2d(encode, &tm_wo, d_in[4], NH * DH, DM, 128, 64, CU_TENSOR_MAP_SWIZZLE_128B);
    encode_2d(encode, &tm_w1, d_in[6], DM, FF, 224, 16, CU_TENSOR_MAP_SWIZZLE_NONE);
    encode_2d(encode, &tm_w2, d_in[8], FF, DM, 256, 8, CU_TENSOR_MAP_SWIZZLE_NONE);
    fused_decode_kernel<<<NCTA, NTHREADS, SMEM_BYTES, cudaStreamPerThread>>>(
        (const __nv_bfloat16*)d_in[0], (const __nv_bfloat16*)d_in[3], (const __nv_bfloat16*)d_in[4], (const __nv_bfloat16*)d_in[7],
        (const __nv_bfloat16*)d_in[9], (__nv_bfloat16*)d_out, tm_k, tm_v, tm_wo, tm_w1, tm_w2);
}
```

```cpp
#include <cuda_runtime.h>
#include <cuda_bf16.h>
#include <cuda.h>
#include <stdint.h>

namespace {

constexpr int NB = 8, DM = 448, NH = 16, SK = 4096, DH = 256, FF = 1792;
constexpr int NCTA = NB * NH;
constexpr int NTAIL = 112;
constexpr int TILE_KEYS = 32;
constexpr int STAGE = TILE_KEYS * DH * 2;
constexpr int NS = 131072 / STAGE;
constexpr int KT = SK / TILE_KEYS;
constexpr int NT = 2 * KT;
constexpr int NTHREADS = 320;
constexpr int XP = 456;
constexpr int SPIN_MAX = 1 << 22;
#define D0 3
#define WIN 448
#define MINF 3
#define WOA_T 255
#define WOB_T 255
#define REDNT 1
#define TSTART 8
#define XA -1
#define XB 1
#define X1W 0
#define EXTRA 128
#define XORM ((page & 1) * 64)
#define OEARLY 4
#define SPRINT 0
#define PFO_T -1
#define X1 0
#define W2_T0 140
#define W2_STEP 12
#define W1_T0 232
#define W1_STEP 4
#define PROF0 288
#define KCYC 0
#define HSLEEP 300
#define ROT 0
#define R1MAP 0
#define W1LATE 0
#define HREP 4
#define GATE_G 0

constexpr int OFF_RING = 0;
constexpr int OFF_WO = OFF_RING + NS * STAGE;
constexpr int OFF_W1 = OFF_WO + DH * 128;
constexpr int OFF_W2 = OFF_W1 + DM * 32;
constexpr int OFF_A = OFF_W2 + FF * 16;
constexpr int OFF_B = OFF_A + SK * 2;
constexpr int OFF_Q = OFF_B + 8960;
constexpr int OFF_C = OFF_Q + 512;
constexpr int OFF_M = OFF_C + NB * XP * 2;
constexpr int OFF_BAR = OFF_M + 256;
constexpr int SMEM_BYTES = OFF_BAR + (2 * NS + 4) * 8;
static_assert(SMEM_BYTES <= 232448, "shared memory budget");

__device__ __align__(128) uint32_t g_epoch[NCTA][32];
__device__ __align__(128) uint32_t g_prog[2][32];
__device__ __align__(128) uint32_t g_q[2][NB * NH * DH / 2];
__device__ __align__(128) uint32_t g_o[2][NH * NB * DH / 2];
__device__ __align__(128) uint32_t g_h[2][HREP][NB * DM / 2];
__device__ __align__(128) uint32_t g_g[2][2 * NTAIL * 32];
__device__ __align__(128) uint32_t g_p2[7 * 16 * 16 * 32];

#define PROF(cond, i)
#define CKDECL
#define CK32(i)
#define CKOUT()

__device__ __forceinline__ uint32_t smem_u32(const void* p) { return (uint32_t)__cvta_generic_to_shared(p); }

__device__ __forceinline__ void mbar_init(uint32_t a, uint32_t c) {
    asm volatile("mbarrier.init.shared.b64 [%0], %1;" :: "r"(a), "r"(c) : "memory");
}
__device__ __forceinline__ void mbar_expect_tx(uint32_t a, uint32_t bytes) {
    asm volatile("mbarrier.arrive.expect_tx.shared.b64 _, [%0], %1;" :: "r"(a), "r"(bytes) : "memory");
}
__device__ __forceinline__ void mbar_arrive(uint32_t a) {
    asm volatile("mbarrier.arrive.shared.b64 _, [%0];" :: "r"(a) : "memory");
}
__device__ __forceinline__ void mbar_arrive2(uint32_t a) {
    asm volatile("mbarrier.arrive.shared.b64 _, [%0], 2;" :: "r"(a) : "memory");
}
__device__ __forceinline__ bool mbar_test(uint32_t a, uint32_t parity) {
    uint32_t ok;
    asm volatile("{\n.reg .pred p;\nmbarrier.test_wait.parity.shared.b64 p, [%1], %2;\nselp.u32 %0, 1, 0, p;\n}"
                 : "=r"(ok) : "r"(a), "r"(parity) : "memory");
    return ok;
}
__device__ __forceinline__ uint32_t clock32() {
    uint32_t c;
    asm volatile("mov.u32 %0, %%clock;" : "=r"(c));
    return c;
}
__device__ __forceinline__ void mbar_wait(uint32_t a, uint32_t parity) {
    uint32_t ok;
    int it = 0;
    do {
        asm volatile("{\n.reg .pred p;\nmbarrier.try_wait.parity.shared.b64 p, [%1], %2;\nselp.u32 %0, 1, 0, p;\n}"
                     : "=r"(ok) : "r"(a), "r"(parity) : "memory");
    } while (!ok && ++it < SPIN_MAX);
}
__device__ __forceinline__ void tma_tile(uint32_t dst, const CUtensorMap* tm, int group, uint32_t bar, uint64_t pol) {
    asm volatile("cp.async.bulk.tensor.4d.shared::cluster.global.mbarrier::complete_tx::bytes.L2::cache_hint"
                 " [%0], [%1, {%3, %3, %3, %4}], [%2], %5;"
                 :: "r"(dst), "l"(tm), "r"(bar), "r"(0), "r"(group), "l"(pol) : "memory");
}
__device__ __forceinline__ void tma_2d(uint32_t dst, const CUtensorMap* tm, int c0, int c1, uint32_t bar) {
    asm volatile("cp.async.bulk.tensor.2d.shared::cluster.global.mbarrier::complete_tx::bytes [%0], [%1, {%3, %4}], [%2];"
                 :: "r"(dst), "l"(tm), "r"(bar), "r"(c0), "r"(c1) : "memory");
}
__device__ __forceinline__ void cbar() { asm volatile("bar.sync 1, 256;" ::: "memory"); }

__device__ __forceinline__ uint4 lds128(uint32_t a) {
    uint4 v;
    asm volatile("ld.shared.v4.u32 {%0,%1,%2,%3}, [%4];" : "=r"(v.x), "=r"(v.y), "=r"(v.z), "=r"(v.w) : "r"(a) : "memory");
    return v;
}
__device__ __forceinline__ uint4 ldm4(uint32_t a) {
    uint4 v;
    asm volatile("ldmatrix.sync.aligned.m8n8.x4.shared.b16 {%0,%1,%2,%3}, [%4];"
                 : "=r"(v.x), "=r"(v.y), "=r"(v.z), "=r"(v.w) : "r"(a) : "memory");
    return v;
}
__device__ __forceinline__ uint4 ldm4t(uint32_t a) {
    uint4 v;
    asm volatile("ldmatrix.sync.aligned.m8n8.x4.trans.shared.b16 {%0,%1,%2,%3}, [%4];"
                 : "=r"(v.x), "=r"(v.y), "=r"(v.z), "=r"(v.w) : "r"(a) : "memory");
    return v;
}
__device__ __forceinline__ void mma16816(float (&c)[4], uint32_t a0, uint32_t a1, uint32_t a2, uint32_t a3, uint32_t b0, uint32_t b1) {
    asm volatile("mma.sync.aligned.m16n8k16.row.col.f32.bf16.bf16.f32 {%0,%1,%2,%3}, {%4,%5,%6,%7}, {%8,%9}, {%0,%1,%2,%3};"
                 : "+f"(c[0]), "+f"(c[1]), "+f"(c[2]), "+f"(c[3])
                 : "r"(a0), "r"(a1), "r"(a2), "r"(a3), "r"(b0), "r"(b1));
}
__device__ __forceinline__ uint4 ld_rlx128(const uint32_t* p) {
    uint4 v;
    asm volatile("ld.relaxed.gpu.global.v4.u32 {%0,%1,%2,%3}, [%4];" : "=r"(v.x), "=r"(v.y), "=r"(v.z), "=r"(v.w) : "l"(p) : "memory");
    return v;
}
__device__ __forceinline__ void ld_rlx128_if(bool c, uint4& v, const uint32_t* p) {
    asm volatile("{\n.reg .pred p;\nsetp.ne.u32 p, %5, 0;\n@p ld.relaxed.gpu.global.v4.u32 {%0,%1,%2,%3}, [%4];\n}"
                 : "+r"(v.x), "+r"(v.y), "+r"(v.z), "+r"(v.w) : "l"(p), "r"((uint32_t)c) : "memory");
}
__device__ __forceinline__ uint32_t ldg32_now(const void* p) {
    uint32_t v;
    asm volatile("ld.global.nc.u32 %0, [%1];" : "=r"(v) : "l"(p) : "memory");
    return v;
}
__device__ __forceinline__ uint4 ldg128_now(const void* p) {
    uint4 v;
    asm volatile("ld.global.nc.v4.u32 {%0,%1,%2,%3}, [%4];" : "=r"(v.x), "=r"(v.y), "=r"(v.z), "=r"(v.w) : "l"(p) : "memory");
    return v;
}
__device__ __forceinline__ void st_rlx32(uint32_t* p, uint32_t v) {
    asm volatile("st.relaxed.gpu.global.u32 [%0], %1;" :: "l"(p), "r"(v) : "memory");
}
__device__ __forceinline__ void st_rlx64(uint32_t* p, uint32_t a, uint32_t b) {
    asm volatile("st.relaxed.gpu.global.v2.u32 [%0], {%1,%2};" :: "l"(p), "r"(a), "r"(b) : "memory");
}

__device__ __forceinline__ void st_rlx32_if(bool c, uint32_t* p, uint32_t v) {
    asm volatile("{\n.reg .pred p;\nsetp.ne.u32 p, %2, 0;\n@p st.relaxed.gpu.global.u32 [%0], %1;\n}"
                 :: "l"(p), "r"(v), "r"((uint32_t)c) : "memory");
}
__device__ __forceinline__ void st_rlx64_if(bool c, uint32_t* p, uint32_t a, uint32_t b) {
    asm volatile("{\n.reg .pred p;\nsetp.ne.u32 p, %3, 0;\n@p st.relaxed.gpu.global.v2.u32 [%0], {%1,%2};\n}"
                 :: "l"(p), "r"(a), "r"(b), "r"((uint32_t)c) : "memory");
}

__device__ __forceinline__ void st_rlx128_if(bool c, uint32_t* p, uint32_t a, uint32_t b, uint32_t d, uint32_t e) {
    asm volatile("{\n.reg .pred p;\nsetp.ne.u32 p, %5, 0;\n@p st.relaxed.gpu.global.v4.u32 [%0], {%1,%2,%3,%4};\n}"
                 :: "l"(p), "r"(a), "r"(b), "r"(d), "r"(e), "r"((uint32_t)c) : "memory");
}
__device__ __forceinline__ float bf_lo(uint32_t w) { return __uint_as_float(w << 16); }
__device__ __forceinline__ float bf_hi(uint32_t w) { return __uint_as_float(w & 0xffff0000u); }
__device__ __forceinline__ uint32_t pack_bf(float lo, float hi) {
    __nv_bfloat162 v = __floats2bfloat162_rn(lo, hi);
    return *reinterpret_cast<uint32_t*>(&v);
}
__device__ __forceinline__ float rbf(float x) { return __uint_as_float(pack_bf(0.f, x)); }
__device__ __forceinline__ uint32_t enc(uint32_t w) { return w == 0xffffffffu ? 0x80008000u : ~w; }
__device__ __forceinline__ uint4 dec4(const uint4& v) { return make_uint4(~v.x, ~v.y, ~v.z, ~v.w); }

__device__ __forceinline__ float warp_sum(float v) {
#pragma unroll
    for (int o = 16; o > 0; o >>= 1) v += __shfl_xor_sync(0xffffffffu, v, o);
    return v;
}

__device__ __forceinline__ void layernorm_row(const uint4& r0, const uint4& r1, int lane, uint32_t dst_row) {
    const bool act = lane < 28;
    float v[16];
    const uint32_t w[8] = {r0.x, r0.y, r0.z, r0.w, r1.x, r1.y, r1.z, r1.w};
#pragma unroll
    for (int i = 0; i < 8; i++) { v[2 * i] = act ? bf_lo(w[i]) : 0.f; v[2 * i + 1] = act ? bf_hi(w[i]) : 0.f; }
    float s = 0.f;
#pragma unroll
    for (int i = 0; i < 16; i++) s += v[i];
    const float mean = warp_sum(s) * (1.0f / DM);
    float q = 0.f;
#pragma unroll
    for (int i = 0; i < 16; i++) { const float d = v[i] - mean; q = fmaf(d, d, q); }
    const float var = warp_sum(act ? q : 0.f) * (1.0f / DM);
    const float mb = rbf(mean);
    const float sd = rbf(sqrtf(rbf(rbf(var) + 1e-5f)));
    const float rs = 1.0f / sd;
    uint32_t o[8];
#pragma unroll
    for (int i = 0; i < 8; i++) o[i] = pack_bf(rbf(v[2 * i] - mb) * rs, rbf(v[2 * i + 1] - mb) * rs);
    if (act) {
        asm volatile("st.shared.v4.u32 [%0], {%1,%2,%3,%4};" :: "r"(dst_row + lane * 16), "r"(o[0]), "r"(o[1]), "r"(o[2]), "r"(o[3]) : "memory");
        asm volatile("st.shared.v4.u32 [%0], {%1,%2,%3,%4};" :: "r"(dst_row + 448 + lane * 16), "r"(o[4]), "r"(o[5]), "r"(o[6]), "r"(o[7]) : "memory");
    }
}

template <class T> __device__ __forceinline__ T* pin(T* p) { asm volatile("" : "+l"(p)); return p; }
__device__ __forceinline__ uint32_t pin(uint32_t v) { asm volatile("" : "+r"(v)); return v; }
__device__ __forceinline__ void sts32(uint32_t a, float v) { asm volatile("st.shared.f32 [%0], %1;" :: "r"(a), "f"(v) : "memory"); }
__device__ __forceinline__ void sts64(uint32_t a, float x, float y) {
    asm volatile("st.shared.v2.f32 [%0], {%1,%2};" :: "r"(a), "f"(x), "f"(y) : "memory");
}
__device__ __forceinline__ void sts128(uint32_t a, float x, float y, float z, float w) {
    asm volatile("st.shared.v4.f32 [%0], {%1,%2,%3,%4};" :: "r"(a), "f"(x), "f"(y), "f"(z), "f"(w) : "memory");
}
__device__ __forceinline__ float lds32f(uint32_t a) {
    float v;
    asm volatile("ld.shared.f32 %0, [%1];" : "=f"(v) : "r"(a) : "memory");
    return v;
}
__device__ __forceinline__ float2 lds64f(uint32_t a) {
    float2 v;
    asm volatile("ld.shared.v2.f32 {%0,%1}, [%2];" : "=f"(v.x), "=f"(v.y) : "r"(a) : "memory");
    return v;
}
__device__ __forceinline__ float4 lds128f(uint32_t a) {
    float4 v;
    asm volatile("ld.shared.v4.f32 {%0,%1,%2,%3}, [%4];" : "=f"(v.x), "=f"(v.y), "=f"(v.z), "=f"(v.w) : "r"(a) : "memory");
    return v;
}
__device__ __forceinline__ uint32_t add_bf2(uint32_t a, uint32_t b) {
    uint32_t d;
    asm("add.rn.bf16x2 %0, %1, %2;" : "=r"(d) : "r"(a), "r"(b));
    return d;
}
__device__ __forceinline__ uint32_t neg_sq_relu_bf2(uint32_t a) {
    uint32_t d;
    asm("{\n.reg .b32 r, n;\nmax.bf16x2 r, %1, %2;\nneg.bf16x2 n, r;\nmul.rn.bf16x2 %0, r, n;\n}" : "=r"(d) : "r"(a), "r"(0));
    return d;
}

#define V4(v) "+r"(v.x), "+r"(v.y), "+r"(v.z), "+r"(v.w)
#define POLL_TAIL(label) \
    "vote.sync.any.pred q, q, 0xffffffff;\nadd.u32 it, it, 1;\nsetp.lt.and.u32 q, it, 4194304, q;\n@!q bra " label "_END;\n"
__device__ __forceinline__ void poll_nz(uint4& v, const uint32_t* p) {
    asm volatile("{\n.reg .pred p0, q;\n.reg .b32 t, it;\nmov.u32 it, 0;\n"
                 "PA:\nmin.u32 t, %0, %1;\nmin.u32 t, t, %2;\nmin.u32 t, t, %3;\nsetp.eq.u32 p0, t, 0;\nmov.pred q, p0;\n"
                 POLL_TAIL("PA")
                 "@p0 ld.relaxed.gpu.global.v4.u32 {%0,%1,%2,%3}, [%4];\nbra PA;\nPA_END:\n}"
                 : V4(v) : "l"(p) : "memory");
}
__device__ __forceinline__ void poll_nz2(uint4& v, uint4& w, const uint32_t* p) {
    asm volatile("{\n.reg .pred p0, p1, q;\n.reg .b32 t, u, it;\nmov.u32 it, 0;\n"
                 "PB:\nmin.u32 t, %0, %1;\nmin.u32 t, t, %2;\nmin.u32 t, t, %3;\nsetp.eq.u32 p0, t, 0;\n"
                 "min.u32 u, %4, %5;\nmin.u32 u, u, %6;\nmin.u32 u, u, %7;\nsetp.eq.u32 p1, u, 0;\nor.pred q, p0, p1;\n"
                 POLL_TAIL("PB")
                 "@p0 ld.relaxed.gpu.global.v4.u32 {%0,%1,%2,%3}, [%8];\n"
                 "@p1 ld.relaxed.gpu.global.v4.u32 {%4,%5,%6,%7}, [%8+512];\nbra PB;\nPB_END:\n}"
                 : V4(v), V4(w) : "l"(p) : "memory");
}
template <int STRIDE, uint32_t MASK>
__device__ __forceinline__ void poll_bit4(uint4& a, uint4& b, uint4& c, uint4& d, const uint32_t* p, uint32_t want) {
    asm volatile("{\n.reg .pred p0, p1, p2, p3, q;\n.reg .b32 t0, t1, t2, t3, u, it;\nmov.u32 it, 0;\n"
                 "PC:\n"
                 "lop3.b32 t0, %0, %1, %17, 0x7e;\nlop3.b32 u, %2, %3, %17, 0x7e;\nlop3.b32 t0, t0, u, %21, 0xa8;\n"
                 "lop3.b32 t1, %4, %5, %17, 0x7e;\nlop3.b32 u, %6, %7, %17, 0x7e;\nlop3.b32 t1, t1, u, %21, 0xa8;\n"
                 "lop3.b32 t2, %8, %9, %17, 0x7e;\nlop3.b32 u, %10, %11, %17, 0x7e;\nlop3.b32 t2, t2, u, %21, 0xa8;\n"
                 "lop3.b32 t3, %12, %13, %17, 0x7e;\nlop3.b32 u, %14, %15, %17, 0x7e;\nlop3.b32 t3, t3, u, %21, 0xa8;\n"
                 "setp.ne.u32 p0, t0, 0;\nsetp.ne.u32 p1, t1, 0;\nsetp.ne.u32 p2, t2, 0;\nsetp.ne.u32 p3, t3, 0;\n"
                 "or.pred q, p0, p1;\nor.pred q, q, p2;\nor.pred q, q, p3;\n"
                 POLL_TAIL("PC")
                 "@p0 ld.relaxed.gpu.global.v4.u32 {%0,%1,%2,%3}, [%16];\n"
                 "@p1 ld.relaxed.gpu.global.v4.u32 {%4,%5,%6,%7}, [%16+%18];\n"
                 "@p2 ld.relaxed.gpu.global.v4.u32 {%8,%9,%10,%11}, [%16+%19];\n"
                 "@p3 ld.relaxed.gpu.global.v4.u32 {%12,%13,%14,%15}, [%16+%20];\nbra PC;\nPC_END:\n}"
                 : V4(a), V4(b), V4(c), V4(d)
                 : "l"(p), "r"(want), "n"(STRIDE), "n"(2 * STRIDE), "n"(3 * STRIDE), "n"(MASK) : "memory");
}

__device__ __forceinline__ void load_x_pair(const __nv_bfloat16* x, int hd, int j, int lane, uint32_t& x0, uint32_t& x1) {
    const __nv_bfloat16* p = x + (hd >> 1) * DM + j * 64 + (hd & 1) * 32 + (lane & 1) * 16 + ((lane & 7) >> 1) * 2;
    x0 = ldg32_now(p);
    x1 = ldg32_now(p + 8);
}
__device__ __forceinline__ const uint32_t* p2_src(int hd, int j, int lane) {
    return g_p2 + ((j * 16 + hd) * 16 + (lane >> 3)) * 32 + (lane & 7) * 4;
}
__device__ __forceinline__ uint32_t* h_dst(uint32_t par, int hd, int j, int lane) {
    return &g_h[par][(lane >> 3) % HREP][(j * 2 + (hd & 1)) * 128 + (hd >> 1) * 16 + (lane & 7) * 2];
}
#define REDUCE_P2(src, dst, tag, x0, x1) do { \
    const uint32_t* src_ = (src); uint32_t* dst_ = (dst); \
    const uint32_t iv = (tag) ^ 1; \
    uint4 v0 = make_uint4(iv, iv, iv, iv), v1 = v0, v2 = v0, v3 = v0; \
    poll_bit4<512, 1u>(v0, v1, v2, v3, src_, tag); \
    CK32(4); \
    float a0 = (__uint_as_float(v0.x) + __uint_as_float(v1.x)) + (__uint_as_float(v2.x) + __uint_as_float(v3.x)); \
    float a1 = (__uint_as_float(v0.y) + __uint_as_float(v1.y)) + (__uint_as_float(v2.y) + __uint_as_float(v3.y)); \
    float a2 = (__uint_as_float(v0.z) + __uint_as_float(v1.z)) + (__uint_as_float(v2.z) + __uint_as_float(v3.z)); \
    float a3 = (__uint_as_float(v0.w) + __uint_as_float(v1.w)) + (__uint_as_float(v2.w) + __uint_as_float(v3.w)); \
    _Pragma("unroll") \
    for (int o = 8; o <= 16; o <<= 1) { \
        a0 += __shfl_xor_sync(0xffffffffu, a0, o); \
        a1 += __shfl_xor_sync(0xffffffffu, a1, o); \
        a2 += __shfl_xor_sync(0xffffffffu, a2, o); \
        a3 += __shfl_xor_sync(0xffffffffu, a3, o); \
    } \
    st_rlx64_if(lane < 8 * HREP, dst_, enc(add_bf2(x0, pack_bf(a0, a1))), enc(add_bf2(x1, pack_bf(a2, a3)))); \
    CK32(5); \
} while (0)

__global__ void __launch_bounds__(NTHREADS, 1)
fused_decode_kernel(const __nv_bfloat16* __restrict__ x, const __nv_bfloat16* __restrict__ wq,
                    const __nv_bfloat16* __restrict__ wo,
                    const __nv_bfloat16* __restrict__ b1, const __nv_bfloat16* __restrict__ b2,
                    __nv_bfloat16* __restrict__ out,
                    const __grid_constant__ CUtensorMap tm_k, const __grid_constant__ CUtensorMap tm_v,
                    const __grid_constant__ CUtensorMap tm_wo, const __grid_constant__ CUtensorMap tm_w1,
                    const __grid_constant__ CUtensorMap tm_w2) {
    extern __shared__ __align__(1024) uint8_t sp[];
    const uint32_t sb = pin(smem_u32(sp));

    const int tid = threadIdx.x, warp = tid >> 5, lane = tid & 31;
    const int cta = blockIdx.x;
    CKDECL;
    const int hd = cta >> 3, bj = cta & 7;
    const bool tail = bj < 7;
    const int r = hd * 7 + bj;
    const int r1 = R1MAP ? bj * 16 + hd : r;
    const uint32_t bar_full = sb + OFF_BAR, bar_empty = bar_full + NS * 8, bar_w = bar_empty + NS * 8;

    const uint32_t s_wq = sb + OFF_WO, s_est = sb + OFF_M + 192;
    uint32_t epoch;
    asm volatile("ld.relaxed.gpu.global.u32 %0, [%1];" : "=r"(epoch) : "l"(g_epoch[cta]) : "memory");
    uint4 xr0 = make_uint4(0, 0, 0, 0), xr1 = xr0;
    if (warp < 8) {
        if (lane < 28) {
            xr0 = ldg128_now(x + warp * DM + lane * 8);
            xr1 = ldg128_now(x + warp * DM + 224 + lane * 8);
        }
        const int row = tid >> 2, ch = tid & 3;
        const uint32_t d = s_wq + row * 64 + ((ch ^ ((row >> 1) & 3)) << 4);
        const __nv_bfloat16* p = wq + (size_t)row * (NH * DH) + cta * 32 + ch * 8;
#pragma unroll
        for (int i = 0; i < 7; i++)
            asm volatile("cp.async.cg.shared.global.L2::128B [%0], [%1], 16;"
                         :: "r"(d + i * 4096), "l"(p + (size_t)i * 64 * (NH * DH)) : "memory");
        asm volatile("bar.arrive 7, %0;" :: "n"(NTHREADS) : "memory");
    }
    const int grp0 = (bj * NH + hd) * (SK / 8);
    const int page = bj * NH + hd, rot = ROT, xorm = XORM;
    uint64_t pol;
    asm volatile("createpolicy.fractional.L2::evict_first.b64 %0, 1.0;" : "=l"(pol));
    PROF(tid == PROF0, 0);
    if (tid == 256) {
        asm volatile("prefetch.tensormap [%0];" :: "l"(&tm_k) : "memory");
#pragma unroll
        for (int s = 0; s < D0; s++) mbar_init(bar_full + s * 8, 1);
        asm volatile("fence.mbarrier_init.release.cluster;" ::: "memory");
        asm volatile("st.volatile.shared.v2.u32 [%0], {%1,%2};" :: "r"(s_est), "r"(0), "r"(clock32()) : "memory");
    }
    if (warp >= 8) { __syncwarp(); asm volatile("bar.sync 7, %0;" :: "n"(NTHREADS) : "memory"); }
    if (tid == 256) {
        const uint32_t c0 = clock32();
        while (clock32() - c0 < KCYC) {}
#pragma unroll
        for (int s = 0; s < D0; s++) {
            mbar_expect_tx(bar_full + s * 8, STAGE);
            tma_tile(sb + OFF_RING + s * STAGE, &tm_k, grp0 + (((s + rot) ^ xorm) & (KT - 1)) * 4, bar_full + s * 8, pol);
        }
    }

    if (warp == 9) {
        uint32_t v = 0;
        const uint32_t* prog = g_prog[(epoch + 1) & 1];
        const uint32_t* qsrc = &g_q[(epoch + 1) & 1][bj * (NH * DH / 2) + hd * (DH / 2) + lane * 4];
        uint4 q = make_uint4(0, 0, 0, 0);
        poll_nz(q, qsrc);
        *reinterpret_cast<uint4*>(sp + OFF_Q + lane * 16) = dec4(q);
        asm volatile("bar.arrive 5, 288;" ::: "memory");
        if (lane == 0) {
#pragma unroll 1
            for (int it = 0; v + WIN < (NT - 1 - SPRINT) * NCTA && it < SPIN_MAX; it++) {
                asm volatile("ld.relaxed.gpu.global.u32 %0, [%1];" : "=r"(v) : "l"(prog) : "memory");
                asm volatile("st.volatile.shared.v2.u32 [%0], {%1,%2};" :: "r"(s_est), "r"(v), "r"(clock32()) : "memory");
                __nanosleep(HSLEEP);
            }
        }
        return;
    }
    if (warp == 8) {
        if (lane == 0) {
#pragma unroll
            for (int s = D0; s < NS; s++) mbar_init(bar_full + s * 8, 1);
#pragma unroll
            for (int s = 0; s < NS; s++) mbar_init(bar_empty + s * 8, 8);
#pragma unroll
            for (int s = 0; s < 4; s++) mbar_init(bar_w + s * 8, 1);
            asm volatile("fence.mbarrier_init.release.cluster;" ::: "memory");
        }
        __syncwarp();
        asm volatile("bar.arrive 3, 288;" ::: "memory");
        uint32_t x0 = 0, x1 = 0;
        if (!REDNT && tail) load_x_pair(x, hd, bj, lane, x0, x1);
        if (lane == 0) {
            asm volatile("prefetch.tensormap [%0];" :: "l"(&tm_v) : "memory");
            asm volatile("prefetch.tensormap [%0];" :: "l"(&tm_wo) : "memory");
            asm volatile("prefetch.tensormap [%0];" :: "l"(&tm_w1) : "memory");
            asm volatile("prefetch.tensormap [%0];" :: "l"(&tm_w2) : "memory");
            uint32_t* prog = g_prog[(epoch + 1) & 1];
            uint32_t t = D0, landed = 0;
#pragma unroll 1
            for (int it = 0; t < NT && it < 16 * SPIN_MAX; it++) {
                if (landed < t && mbar_test(bar_full + (landed & (NS - 1)) * 8, (landed / NS) & 1)) {
                    landed++;
                    if (((landed + cta) & 3) == 0) asm volatile("red.relaxed.gpu.global.add.u32 [%0], 4;" :: "l"(prog) : "memory");
                }
                if (t - landed >= NS) continue;
                if (t < TSTART && t - landed >= (landed ? MINF : D0)) continue;
                if (t - landed >= MINF - 1 && t >= TSTART && t < NT - SPRINT) {
                    uint32_t v, c0;
                    asm volatile("ld.volatile.shared.v2.u32 {%0,%1}, [%2];" : "=r"(v), "=r"(c0) : "r"(s_est) : "memory");
                    if (t * NCTA > v + min(((clock32() - c0) * 7) >> 6, 256u) + (t - landed >= MINF ? WIN : WIN + EXTRA)) continue;
                }
                const uint32_t s = t & (NS - 1);
                if (t >= NS && !mbar_test(bar_empty + s * 8, (t / NS - 1) & 1)) continue;
                mbar_expect_tx(bar_full + s * 8, STAGE);
                tma_tile(sb + OFF_RING + s * STAGE, t < KT ? &tm_k : &tm_v, grp0 + (((t + rot) ^ xorm) & (KT - 1)) * 4, bar_full + s * 8, pol);
                if (PFO_T >= 0 && t == PFO_T)
                    asm volatile("cp.async.bulk.prefetch.L2.global [%0], %1;" :: "l"(wo + (size_t)cta * (32 * DM)), "r"(32 * DM * 2) : "memory");
                if (tail) {
                    if (XA < 0 && t == WOA_T) {
                        mbar_expect_tx(bar_w, 128 * 128);
                        tma_2d(sb + OFF_WO, &tm_wo, bj * 64, hd * DH, bar_w);
                    }
                    if (XB < 0 && t == WOB_T) {
                        mbar_expect_tx(bar_w + 24, 128 * 128);
                        tma_2d(sb + OFF_WO + 128 * 128, &tm_wo, bj * 64, hd * DH + 128, bar_w + 24);
                    }
                    if (!W1LATE && X1 < 0) {
                        if (t == W1_T0) mbar_expect_tx(bar_w + 8, DM * 32);
#pragma unroll
                        for (int i = 0; i < 2; i++)
                            if (t == W1_T0 + i * W1_STEP) tma_2d(sb + OFF_W1 + i * 224 * 32, &tm_w1, r1 * 16, i * 224, bar_w + 8);
                    }
                    if (t == W2_T0) mbar_expect_tx(bar_w + 16, FF * 16);
#pragma unroll
                    for (int i = 0; i < 7; i++)
                        if (t == W2_T0 + i * W2_STEP) tma_2d(sb + OFF_W2 + i * 4096, &tm_w2, (r >> 1) * 8, i * 256, bar_w + 16);
                }
                t++;
            }
            asm volatile("red.relaxed.gpu.global.add.u32 [%0], %1;" :: "l"(prog), "r"(NT - ((landed + (cta & 3)) & ~3u)) : "memory");
            if (XA >= 0 && tail) {
                mbar_wait(bar_full + ((NT - 1 - XA) & (NS - 1)) * 8, ((NT - 1 - XA) / NS) & 1);
                mbar_expect_tx(bar_w, 128 * 128);
                tma_2d(sb + OFF_WO, &tm_wo, bj * 64, hd * DH, bar_w);
            }
            if (XB >= 0 && tail) {
                mbar_wait(bar_full + ((NT - 1 - XB) & (NS - 1)) * 8, ((NT - 1 - XB) / NS) & 1);
                mbar_expect_tx(bar_w + 24, 128 * 128);
                tma_2d(sb + OFF_WO + 128 * 128, &tm_wo, bj * 64, hd * DH + 128, bar_w + 24);
            }
            if (X1 >= 0 && tail) {
                if (X1W) mbar_wait(bar_w + 24, 0);
                mbar_wait(bar_full + ((NT - 1 - X1) & (NS - 1)) * 8, ((NT - 1 - X1) / NS) & 1);
                mbar_expect_tx(bar_w + 8, DM * 32);
                tma_2d(sb + OFF_W1, &tm_w1, r1 * 16, 0, bar_w + 8);
                tma_2d(sb + OFF_W1 + 224 * 32, &tm_w1, r1 * 16, 224, bar_w + 8);
            }
        }
        __syncwarp();
        if (!REDNT && tail) {
            const uint32_t tag = (epoch + 1) & 1;
            REDUCE_P2(pin(p2_src(hd, bj, lane)), pin(h_dst(tag, hd, bj, lane)), tag, x0, x1);
            CKOUT();
        }
        return;
    }

    const int g = lane >> 2, t4 = lane & 3;
    asm volatile("cp.async.commit_group;" ::: "memory");
    const uint32_t par = (epoch + 1) & 1;
    const int bg = r & 1, cg = r >> 1;
    uint32_t bias1a = 0, bias1b = 0, bias2w = 0;
    if (warp == 7 && tail) {
        bias1a = ldg32_now(b1 + r1 * 16 + t4 * 2);
        bias1b = ldg32_now(b1 + r1 * 16 + 8 + t4 * 2);
        bias2w = ldg32_now(b2 + cg * 8 + (lane & 6)) >> ((lane & 1) * 16);
    }
    if (REDNT && !tail && warp < 7) load_x_pair(x, hd, warp, lane, bias1a, bias1b);

    layernorm_row(xr0, xr1, lane, sb + OFF_C + warp * (XP * 2));
    asm volatile("cp.async.wait_group 0;" ::: "memory");
    asm volatile("bar.sync 3, 288;" ::: "memory");

    float* red_b = reinterpret_cast<float*>(sp + OFF_B);
    if (warp < 7) {
        float acc[4][4] = {};
#pragma unroll
        for (int p = 0; p < 2; p++) {
            const uint4 a = ldm4(sb + OFF_C + (lane & 7) * (XP * 2) + (warp * 64 + p * 32 + (lane >> 3) * 8) * 2);
#pragma unroll
            for (int s = 0; s < 2; s++) {
                const int row = warp * 64 + p * 32 + s * 16 + ((lane >> 3) & 1) * 8 + (lane & 7);
#pragma unroll
                for (int np = 0; np < 2; np++) {
                    const int ch = np * 2 + (lane >> 4);
                    const uint4 bw = ldm4t(s_wq + row * 64 + ((ch ^ ((row >> 1) & 3)) << 4));
                    mma16816(acc[np * 2], s ? a.z : a.x, 0, s ? a.w : a.y, 0, bw.x, bw.y);
                    mma16816(acc[np * 2 + 1], s ? a.z : a.x, 0, s ? a.w : a.y, 0, bw.z, bw.w);
                }
            }
        }
#pragma unroll
        for (int n = 0; n < 4; n++)
            *reinterpret_cast<float2*>(red_b + (warp * 8 + g) * 40 + n * 8 + t4 * 2) = make_float2(acc[n][0], acc[n][1]);
    }
    asm volatile("fence.proxy.async.shared::cta;" ::: "memory");
    cbar();
    if (tid < 128) {
        const int b = tid >> 4, wd = tid & 15;
        float s0 = 0.f, s1 = 0.f;
#pragma unroll
        for (int w = 0; w < 7; w++) {
            const float2 p = *reinterpret_cast<const float2*>(red_b + (w * 8 + b) * 40 + wd * 2);
            s0 += p.x; s1 += p.y;
        }
        st_rlx32(&g_q[par][b * (NH * DH / 2) + cta * 16 + (wd & 3) * 4 + ((wd >> 2) & 1) * 2 + (wd >> 3)], enc(pack_bf(s0, s1)));
    } else {
        const int i = tid - 128;
        g_q[par ^ 1][(i >> 4) * (NH * DH / 2) + cta * 16 + (i & 15)] = 0;
        g_o[par ^ 1][cta * 128 + i] = 0;
        if (cta == 0 && i == 0) g_prog[par ^ 1][0] = 0;
        if (tail && i < 64) g_g[par ^ 1][((i >> 5) * NTAIL + r1) * 32 + (i & 31)] = 0;
        if (tail && i < 16 * HREP) g_h[par ^ 1][i >> 4][(bj * 2 + (hd & 1)) * 128 + (hd >> 1) * 16 + (i & 15)] = 0;
    }
    PROF(tid == 0, 1);

    uint32_t* const p_o_st = pin(&g_o[par][(hd * 8 + warp) * 128 + bj * 16 + t4 * 4]);
    const uint32_t* const p_o_ld = pin(&g_o[par][(hd * 8 + warp) * 128 + lane * 4]);
    uint32_t* const p_p2_st = pin(g_p2 + ((bj * 16 + warp * 2 + (lane >> 4)) * 16 + hd) * 32 + (lane & 15) * 2);
    const uint32_t* const p_h_ld = pin(tail ? &g_h[par][cta % HREP][warp * 256 + lane * 4] : p2_src(hd, warp, lane));
    uint32_t* const p_g_st = pin(tail ? &g_g[par][((g >> 2) * NTAIL + r1) * 32 + (g & 3) * 8 + t4 * 2] : h_dst(par, hd, warp, lane));
    const uint32_t* const p_g_ld =
        pin(&g_g[par][(bg * NTAIL + warp * 16 + (g >> 2) * 8 + (t4 >> 1)) * 32 + (g & 3) * 8 + (t4 & 1) * 4]);
    __nv_bfloat16* const p_out = pin(out + (bg * 4 + (lane >> 3)) * DM + cg * 8 + (lane & 7));
    const uint32_t a_wo = pin(sb + OFF_WO + (warp * 32 + (lane >> 4) * 8 + (lane & 7)) * 128 + ((((lane >> 3) & 1) ^ (lane & 7)) << 4));
    const uint32_t a_w1 = pin(sb + OFF_W1 + (((lane >> 3) & 1) * 8 + (lane & 7)) * 32 + (lane >> 4) * 16);
    const uint32_t a_w2 = pin(sb + OFF_W2 + (warp * 256 + ((lane >> 3) & 1) * 128 + ((lane >> 2) & 1) * 16 + (lane >> 4) * 8 +
                                             ((lane >> 1) & 1) * 4 + (lane & 1)) * 16);
    const uint32_t o_r2w = pin((uint32_t)(((warp * 8 + t4 * 2) * 68 + g) * 4));
    const uint32_t o_r2r = pin((uint32_t)((warp * 68 + (lane >> 4) * 32 + ((lane >> 1) & 1) * 16 + (lane & 1) * 8 + ((lane >> 2) & 3) * 2) * 4));
    const uint32_t a_r4 = pin(sb + OFF_C + lane * 16);
    const uint32_t a_st = pin(sb + OFF_C + 4096 + g * 8);
    const uint32_t a_r5 = pin(sb + OFF_C + 5120 + (warp < 7 ? warp * 128 + ((t4 & 1) * 16 + g) * 4 : lane * 4));
    const uint32_t a_hres = pin(sb + OFF_M + 64 + (warp < 7 ? lane * 4 : (bg * 4 + (lane >> 3)) * 16 + (lane & 7) * 2));
    __nv_bfloat16* sc = reinterpret_cast<__nv_bfloat16*>(sp + OFF_A);

    {
        float oa[4][4] = {}, ob[4][4] = {};
        uint4 ov = make_uint4(0, 0, 0, 0);
        {
            uint4 q[8];
            {
                asm volatile("bar.sync 5, 288;" ::: "memory");
#pragma unroll
                for (int i = 0; i < 8; i++) q[i] = lds128(sb + OFF_Q + i * 64 + t4 * 16);
            }
            PROF(tid == 0, 2);

            float mx = -INFINITY;
            {
                const uint32_t ka = pin(sb + OFF_RING + (warp & 3) * 4096 + (lane & 7) * 128 + (((lane >> 3) ^ (lane & 7)) << 4));
                uint32_t* scw = reinterpret_cast<uint32_t*>(sc) + t4 * 4 + (warp & 1) * 2 + ((warp >> 1) & 1);
#pragma unroll 1
                for (int t = warp >> 2; t < KT; t += 2) {
                    const int st = t & (NS - 1);
                    mbar_wait(bar_full + st * 8, (t / NS) & 1);
                    uint4 kf[8];
#pragma unroll
                    for (int i = 0; i < 8; i++) kf[i] = ldm4((ka ^ ((i & 1) << 6)) + st * STAGE + (i >> 1) * 1024);
                    float c[4][4] = {};
#pragma unroll
                    for (int i = 0; i < 8; i++) {
                        mma16816(c[(i & 1) * 2], q[i].x, q[i].y, q[i].z, q[i].w, kf[i].x, kf[i].y);
                        mma16816(c[(i & 1) * 2 + 1], q[i].x, q[i].y, q[i].z, q[i].w, kf[i].z, kf[i].w);
                    }
                    if (lane == 0) mbar_arrive2(bar_empty + st * 8);
                    const uint32_t d = pack_bf((c[0][0] + c[2][0]) + (c[1][2] + c[3][2]), (c[0][1] + c[2][1]) + (c[1][3] + c[3][3]));
                    const uint32_t sw = pack_bf(bf_lo(d) * 0.0625f, bf_hi(d) * 0.0625f);
                    mx = fmaxf(mx, fmaxf(bf_lo(sw), bf_hi(sw)));
                    if (lane < 4) scw[t * 16] = sw;
                }
            }
            PROF(tid == 0, 3);

            float* sm_m = reinterpret_cast<float*>(sp + OFF_M);
            mx = fmaxf(mx, __shfl_xor_sync(0xffffffffu, mx, 1));
            mx = fmaxf(mx, __shfl_xor_sync(0xffffffffu, mx, 2));
            if (lane == 0) sm_m[warp] = mx;
            cbar();
#pragma unroll
            for (int w = 0; w < 8; w++) mx = fmaxf(mx, sm_m[w]);
            {
                float e[16], sum = 0.f;
#pragma unroll
                for (int i = 0; i < 4; i++) {
                    const uint2 s = *reinterpret_cast<const uint2*>(sc + i * 1024 + tid * 4);
                    e[i * 4 + 0] = expf(bf_lo(s.x) - mx); e[i * 4 + 1] = expf(bf_hi(s.x) - mx);
                    e[i * 4 + 2] = expf(bf_lo(s.y) - mx); e[i * 4 + 3] = expf(bf_hi(s.y) - mx);
                    sum += (e[i * 4] + e[i * 4 + 1]) + (e[i * 4 + 2] + e[i * 4 + 3]);
                }
                sum = warp_sum(sum);
                if (lane == 0) sm_m[8 + warp] = sum;
                cbar();
                sum = 0.f;
#pragma unroll
                for (int w = 0; w < 8; w++) sum += sm_m[8 + w];
                const float inv = 1.0f / sum;
#pragma unroll
                for (int i = 0; i < 4; i++)
                    *reinterpret_cast<uint2*>(sc + i * 1024 + tid * 4) =
                        make_uint2(pack_bf(e[i * 4] * inv, e[i * 4 + 1] * inv), pack_bf(e[i * 4 + 2] * inv, e[i * 4 + 3] * inv));
                cbar();
            }
            CK32(11);
            PROF(tid == 0, 4);

            if (tid == 0) st_rlx32(g_epoch[cta], epoch + 1);

            const uint32_t va = pin(sb + OFF_RING + ((lane >> 3) & 1) * 4096 + (warp >> 1) * 1024 + (lane & 7) * 128 +
                                    ((((warp & 1) * 4 + (lane >> 4)) ^ (lane & 7)) << 4));
            auto pv_tile = [&](int t) {
                const int st = t & (NS - 1);
                const uint4 p = lds128(sb + OFF_A + t * 64 + t4 * 16);
                const uint32_t va0 = pin(va + st * STAGE), va1 = pin(va0 ^ 32);
                mbar_wait(bar_full + st * 8, ((KT + t) / NS) & 1);
                const uint4 v0 = ldm4t(va0), v1 = ldm4t(va1), v2 = ldm4t(va0 + 8192), v3 = ldm4t(va1 + 8192);
                mma16816(oa[0], p.x, p.y, p.z, p.w, v0.x, v0.y);
                mma16816(oa[1], p.x, p.y, p.z, p.w, v0.z, v0.w);
                mma16816(oa[2], p.x, p.y, p.z, p.w, v1.x, v1.y);
                mma16816(oa[3], p.x, p.y, p.z, p.w, v1.z, v1.w);
                mma16816(ob[0], p.x, p.y, p.z, p.w, v2.x, v2.y);
                mma16816(ob[1], p.x, p.y, p.z, p.w, v2.z, v2.w);
                mma16816(ob[2], p.x, p.y, p.z, p.w, v3.x, v3.y);
                mma16816(ob[3], p.x, p.y, p.z, p.w, v3.z, v3.w);
                if (lane == 0) mbar_arrive(bar_empty + st * 8);
            };
#pragma unroll 1
            for (int t = 0; t < KT - OEARLY; t++) pv_tile(t);
            if (OEARLY) ld_rlx128_if(tail, ov, p_o_ld);
#pragma unroll 1
            for (int t = KT - OEARLY; t < KT; t++) pv_tile(t);
            CK32(0);
        }

        st_rlx128_if(lane < 4, p_o_st,
                     enc(pack_bf(oa[0][0] + ob[0][2], oa[0][1] + ob[0][3])), enc(pack_bf(oa[1][0] + ob[1][2], oa[1][1] + ob[1][3])),
                     enc(pack_bf(oa[2][0] + ob[2][2], oa[2][1] + ob[2][3])), enc(pack_bf(oa[3][0] + ob[3][2], oa[3][1] + ob[3][3])));
        CK32(1);
        if (!tail) {
            if (REDNT && warp < 7) REDUCE_P2(p_h_ld, p_g_st, par, bias1a, bias1b);
            CKOUT();
            return;
        }

        {
            const uint32_t red_a = sb + OFF_RING + ((NT - 3) % NS) * STAGE;
            uint4 v = ov;
            ld_rlx128_if(min(min(v.x, v.y), min(v.z, v.w)) == 0, v, p_o_ld);
            mbar_wait(bar_w + (warp >> 2) * 24, 0);
            mbar_wait(bar_empty + ((NT - 3) % NS) * 8, ((NT - 3) / NS) & 1);
            mbar_wait(bar_empty + ((NT - 2) % NS) * 8, ((NT - 2) / NS) & 1);
            uint4 a[2][4];
#pragma unroll
            for (int s = 0; s < 2; s++)
#pragma unroll
                for (int mt = 0; mt < 4; mt++) a[s][mt] = ldm4t((a_wo ^ (mt << 5)) + s * 2048);
            poll_nz(v, p_o_ld);
            CK32(2);
            v = dec4(v);
            float acc[4][4] = {};
#pragma unroll
            for (int mt = 0; mt < 4; mt++) mma16816(acc[mt], a[0][mt].x, a[0][mt].y, a[0][mt].z, a[0][mt].w, v.x, v.y);
#pragma unroll
            for (int mt = 0; mt < 4; mt++) mma16816(acc[mt], a[1][mt].x, a[1][mt].y, a[1][mt].z, a[1][mt].w, v.z, v.w);
#pragma unroll
            for (int mt = 0; mt < 4; mt++) {
                sts32(red_a + o_r2w + mt * 64, acc[mt][0]);
                sts32(red_a + o_r2w + mt * 64 + 272, acc[mt][1]);
                sts32(red_a + o_r2w + mt * 64 + 32, acc[mt][2]);
                sts32(red_a + o_r2w + mt * 64 + 304, acc[mt][3]);
            }
            cbar();
            float2 p[8];
#pragma unroll
            for (int w = 0; w < 8; w++) p[w] = lds64f(red_a + o_r2r + w * (8 * 272));
            const float s0 = ((p[0].x + p[1].x) + (p[2].x + p[3].x)) + ((p[4].x + p[5].x) + (p[6].x + p[7].x));
            const float s1 = ((p[0].y + p[1].y) + (p[2].y + p[3].y)) + ((p[4].y + p[5].y) + (p[6].y + p[7].y));
            st_rlx64(p_p2_st, (__float_as_uint(s0) & ~1u) | par, (__float_as_uint(s1) & ~1u) | par);
        }
        CK32(3);

        constexpr uint32_t ONES = 0x3f803f80u;
        if (warp < 7) {
            uint4 v0 = ld_rlx128(p_h_ld), v1 = ld_rlx128(p_h_ld + 128);
            mbar_wait(bar_w + 16, 0);
            uint4 aw[8];
#pragma unroll
            for (int s = 0; s < 8; s++) aw[s] = ldm4t(a_w2 + (s >> 1) * 512 + (s & 1) * 32);
            mbar_wait(bar_w + 8, 0);
            uint4 bw[4];
#pragma unroll
            for (int s = 0; s < 4; s++) bw[s] = ldm4t(a_w1 + warp * 2048 + s * 512);
            poll_nz2(v0, v1, p_h_ld);
            CK32(6);
            v0 = dec4(v0); v1 = dec4(v1);
            const uint32_t hw[8] = {v0.x, v0.y, v0.z, v0.w, v1.x, v1.y, v1.z, v1.w};
            float c0[4] = {}, c1[4] = {}, cs[4] = {};
#pragma unroll
            for (int s = 0; s < 4; s++) {
                mma16816(cs, hw[2 * s], ONES, hw[2 * s + 1], ONES, hw[2 * s], hw[2 * s + 1]);
                mma16816(c0, hw[2 * s], ONES, hw[2 * s + 1], ONES, bw[s].x, bw[s].y);
                mma16816(c1, hw[2 * s], ONES, hw[2 * s + 1], ONES, bw[s].z, bw[s].w);
            }
            if (warp == (cg >> 3)) {
                const uint4 hv = (cg & 4) ? v1 : v0;
                const uint32_t hx = (cg & 2) ? ((cg & 1) ? hv.w : hv.z) : ((cg & 1) ? hv.y : hv.x);
                sts32(a_hres, __uint_as_float(hx));
            }
            if (t4 == (g >> 1)) sts64(a_st + warp * 64, (g & 1) ? cs[3] : cs[2], (g & 1) ? cs[1] : cs[0]);
            sts128(a_r4 + warp * 512, c0[0], c0[1], c1[0], c1[1]);
            asm volatile("bar.arrive 2, 256;" ::: "memory");
            CK32(7);

            if (GATE_G) asm volatile("bar.sync 6, 256;" ::: "memory");
            uint4 u0 = ld_rlx128(p_g_ld), u1 = ld_rlx128(p_g_ld + 64), u2 = ld_rlx128(p_g_ld + 128), u3 = ld_rlx128(p_g_ld + 192);
            poll_bit4<256, 0x80000000u>(u0, u1, u2, u3, p_g_ld, 0x80000000u);
            CK32(9);
            float y0[4] = {}, y1[4] = {}, y2[4] = {}, y3[4] = {};
            mma16816(y0, aw[0].x, aw[0].y, aw[0].z, aw[0].w, u0.x, u0.y);
            mma16816(y1, aw[2].x, aw[2].y, aw[2].z, aw[2].w, u1.x, u1.y);
            mma16816(y2, aw[4].x, aw[4].y, aw[4].z, aw[4].w, u2.x, u2.y);
            mma16816(y3, aw[6].x, aw[6].y, aw[6].z, aw[6].w, u3.x, u3.y);
            mma16816(y0, aw[1].x, aw[1].y, aw[1].z, aw[1].w, u0.z, u0.w);
            mma16816(y1, aw[3].x, aw[3].y, aw[3].z, aw[3].w, u1.z, u1.w);
            mma16816(y2, aw[5].x, aw[5].y, aw[5].z, aw[5].w, u2.z, u2.w);
            mma16816(y3, aw[7].x, aw[7].y, aw[7].z, aw[7].w, u3.z, u3.w);
            const bool lo = t4 < 2;
            const float z0 = ((lo ? y0[0] : y0[2]) + (lo ? y1[0] : y1[2])) + ((lo ? y2[0] : y2[2]) + (lo ? y3[0] : y3[2]));
            const float z1 = ((lo ? y0[1] : y0[3]) + (lo ? y1[1] : y1[3])) + ((lo ? y2[1] : y2[3]) + (lo ? y3[1] : y3[3]));
            sts32(a_r5 + (lo ? 0 : 896), z0);
            sts32(a_r5 + (lo ? 32 : 928), z1);
            asm volatile("bar.arrive 4, 256;" ::: "memory");
        } else {
            float w0[4] = {}, w1s[4] = {}, w2s[4] = {}, w3s[4] = {};
            if (W1LATE && lane == 0) {
                mbar_expect_tx(bar_w + 8, DM * 32);
                tma_2d(sb + OFF_W1, &tm_w1, r1 * 16, 0, bar_w + 8);
                tma_2d(sb + OFF_W1 + 224 * 32, &tm_w1, r1 * 16, 224, bar_w + 8);
            }
            __syncwarp();
            mbar_wait(bar_w + 8, 0);
#pragma unroll 1
            for (int s = 0; s < 28; s += 14) {
                uint4 bw[14];
#pragma unroll
                for (int i = 0; i < 14; i++) bw[i] = ldm4t(a_w1 + (s + i) * 512);
#pragma unroll
                for (int i = 0; i < 14; i += 2) {
                    mma16816(w0, ONES, ONES, ONES, ONES, bw[i].x, bw[i].y);
                    mma16816(w1s, ONES, ONES, ONES, ONES, bw[i].z, bw[i].w);
                    mma16816(w2s, ONES, ONES, ONES, ONES, bw[i + 1].x, bw[i + 1].y);
                    mma16816(w3s, ONES, ONES, ONES, ONES, bw[i + 1].z, bw[i + 1].w);
                }
            }
            w0[0] += w2s[0]; w0[1] += w2s[1]; w1s[0] += w3s[0]; w1s[1] += w3s[1];
            asm volatile("bar.sync 2, 256;" ::: "memory");
            float2 sq[7];
            float4 p[7];
#pragma unroll
            for (int w = 0; w < 7; w++) sq[w] = lds64f(a_st + w * 64);
#pragma unroll
            for (int w = 0; w < 7; w++) p[w] = lds128f(a_r4 + w * 512);
            const float mean = (((sq[0].x + sq[1].x) + (sq[2].x + sq[3].x)) + ((sq[4].x + sq[5].x) + sq[6].x)) * (1.0f / DM);
            const float msq = (((sq[0].y + sq[1].y) + (sq[2].y + sq[3].y)) + ((sq[4].y + sq[5].y) + sq[6].y)) * (1.0f / DM);
            const float var = fmaxf(fmaf(-mean, mean, msq), 0.f);
            float sd, rs;
            asm("sqrt.approx.ftz.f32 %0, %1;" : "=f"(sd) : "f"(rbf(rbf(var) + 1e-5f)));
            asm("rcp.approx.ftz.f32 %0, %1;" : "=f"(rs) : "f"(rbf(sd)));
            const float mb = rbf(mean);
            const float s0 = fmaf(-mb, w0[0], ((p[0].x + p[1].x) + (p[2].x + p[3].x)) + ((p[4].x + p[5].x) + p[6].x));
            const float s1 = fmaf(-mb, w0[1], ((p[0].y + p[1].y) + (p[2].y + p[3].y)) + ((p[4].y + p[5].y) + p[6].y));
            const float s2 = fmaf(-mb, w1s[0], ((p[0].z + p[1].z) + (p[2].z + p[3].z)) + ((p[4].z + p[5].z) + p[6].z));
            const float s3 = fmaf(-mb, w1s[1], ((p[0].w + p[1].w) + (p[2].w + p[3].w)) + ((p[4].w + p[5].w) + p[6].w));
            st_rlx64(p_g_st, neg_sq_relu_bf2(add_bf2(pack_bf(s0 * rs, s1 * rs), bias1a)),
                        neg_sq_relu_bf2(add_bf2(pack_bf(s2 * rs, s3 * rs), bias1b)));
            if (GATE_G) asm volatile("bar.arrive 6, 256;" ::: "memory");
            CK32(8);
            uint16_t hraw;
            asm volatile("ld.shared.u16 %0, [%1];" : "=h"(hraw) : "r"(a_hres) : "memory");
            asm volatile("bar.sync 4, 256;" ::: "memory");
            float y[14];
#pragma unroll
            for (int w = 0; w < 14; w++) y[w] = lds32f(a_r5 + w * 128);
            const float ys = (((y[0] + y[1]) + (y[2] + y[3])) + ((y[4] + y[5]) + (y[6] + y[7]))) +
                             (((y[8] + y[9]) + (y[10] + y[11])) + (y[12] + y[13]));
            const uint32_t res = add_bf2(hraw, add_bf2(pack_bf(-ys, 0.f), bias2w));
            asm volatile("st.global.u16 [%0], %1;" :: "l"(p_out), "h"((uint16_t)res) : "memory");
            CK32(10);
        }
        CKOUT();
    }
}

typedef CUresult (*EncodeTiledFn)(CUtensorMap*, CUtensorMapDataType, cuuint32_t, void*, const cuuint64_t*,
                                  const cuuint64_t*, const cuuint32_t*, const cuuint32_t*, CUtensorMapInterleave,
                                  CUtensorMapSwizzle, CUtensorMapL2promotion, CUtensorMapFloatOOBfill);

void encode_2d(EncodeTiledFn fn, CUtensorMap* tm, void* base, int rows, int cols, int box_rows, int box_cols,
               CUtensorMapSwizzle sw) {
    cuuint64_t dims[2] = {(cuuint64_t)cols, (cuuint64_t)rows};
    cuuint64_t strides[1] = {(cuuint64_t)cols * 2};
    cuuint32_t box[2] = {(cuuint32_t)box_cols, (cuuint32_t)box_rows};
    cuuint32_t es[2] = {1, 1};
    fn(tm, CU_TENSOR_MAP_DATA_TYPE_BFLOAT16, 2, base, dims, strides, box, es, CU_TENSOR_MAP_INTERLEAVE_NONE, sw,
       CU_TENSOR_MAP_L2_PROMOTION_L2_128B, CU_TENSOR_MAP_FLOAT_OOB_FILL_NONE);
}

void encode_kv(EncodeTiledFn fn, CUtensorMap* tm, void* base) {
    cuuint64_t dims[4] = {64, 8, 4, (cuuint64_t)NB * NH * SK / 8};
    cuuint64_t strides[3] = {DH * 2, 128, 8 * DH * 2};
    cuuint32_t box[4] = {64, 8, 4, TILE_KEYS / 8};
    cuuint32_t es[4] = {1, 1, 1, 1};
    fn(tm, CU_TENSOR_MAP_DATA_TYPE_BFLOAT16, 4, base, dims, strides, box, es, CU_TENSOR_MAP_INTERLEAVE_NONE,
       CU_TENSOR_MAP_SWIZZLE_128B, CU_TENSOR_MAP_L2_PROMOTION_NONE, CU_TENSOR_MAP_FLOAT_OOB_FILL_NONE);
}

}

extern "C" void kernel_launch(void* const* d_in, const int* in_sizes, int n_in, void* d_out, int out_size) {
    (void)in_sizes; (void)n_in; (void)out_size;
    static EncodeTiledFn encode = nullptr;
    if (!encode) {
        void* fn = nullptr;
        cudaDriverEntryPointQueryResult qr;
        cudaGetDriverEntryPoint("cuTensorMapEncodeTiled", &fn, cudaEnableDefault, &qr);
        encode = (EncodeTiledFn)fn;
        cudaFuncSetAttribute(fused_decode_kernel, cudaFuncAttributeMaxDynamicSharedMemorySize, SMEM_BYTES);
    }
    CUtensorMap tm_k, tm_v, tm_wo, tm_w1, tm_w2;
    encode_kv(encode, &tm_k, d_in[1]);
    encode_kv(encode, &tm_v, d_in[2]);
    encode_2d(encode, &tm_wo, d_in[4], NH * DH, DM, 128, 64, CU_TENSOR_MAP_SWIZZLE_128B);
    encode_2d(encode, &tm_w1, d_in[6], DM, FF, 224, 16, CU_TENSOR_MAP_SWIZZLE_NONE);
    encode_2d(encode, &tm_w2, d_in[8], FF, DM, 256, 8, CU_TENSOR_MAP_SWIZZLE_NONE);
    fused_decode_kernel<<<NCTA, NTHREADS, SMEM_BYTES, cudaStreamPerThread>>>(
        (const __nv_bfloat16*)d_in[0], (const __nv_bfloat16*)d_in[3], (const __nv_bfloat16*)d_in[4], (const __nv_bfloat16*)d_in[7],
        (const __nv_bfloat16*)d_in[9], (__nv_bfloat16*)d_out, tm_k, tm_v, tm_wo, tm_w1, tm_w2);
}
```

```cpp
#include <cuda_runtime.h>
#include <cuda_bf16.h>
#include <cuda.h>
#include <stdint.h>

namespace {

constexpr int NB = 8, DM = 448, NH = 16, SK = 4096, DH = 256, FF = 1792;
constexpr int NCTA = NB * NH;
constexpr int NMSG = FF / 16;
constexpr int TILE_KEYS = 32;
constexpr int STAGE = TILE_KEYS * DH * 2;
constexpr int NS = 8;
constexpr int KT = SK / TILE_KEYS;
constexpr int NT = 2 * KT;
constexpr int NTHREADS = 320;
constexpr int XP = 456;
constexpr int SPIN_MAX = 1 << 22;

#define WIN 416
#define EXTRA 192
#define XO 2
#define X1 0
#define HREP 2
#define OEARLY 3
constexpr int D0 = 3;
constexpr int HSLEEP = 300;

constexpr int OFF_RING = 0;
constexpr int OFF_WO = OFF_RING + NS * STAGE;
constexpr int OFF_W = OFF_WO + DH * 128;
constexpr int OFF_A = OFF_W + DM * 64;
constexpr int OFF_B = OFF_A + SK * 2;
constexpr int OFF_Q = OFF_B + 8960;
constexpr int OFF_C = OFF_Q + 512;
constexpr int OFF_M = OFF_C + NB * XP * 2;
constexpr int OFF_BAR = OFF_M + 128;
constexpr int SMEM_BYTES = OFF_BAR + (2 * NS + 9) * 8;
static_assert(SMEM_BYTES <= 232448, "shared memory budget");

__device__ __align__(128) uint32_t g_epoch[NCTA][32];
__device__ __align__(128) uint32_t g_prog[2][32];
__device__ __align__(128) uint32_t g_q[2][NB * NH * DH / 2];
__device__ __align__(128) uint32_t g_o[2][NH * NB * DH / 2];
__device__ __align__(128) uint32_t g_h[2][HREP][NB * DM / 2];
__device__ __align__(128) uint32_t g_g[2][2 * NMSG * 32];
__device__ __align__(128) uint32_t g_p2[7 * 16 * 16 * 32];

#define PROF(cond, i)
#define CKDECL
#define CK32(i)
#define CKOUT()

__device__ __forceinline__ uint32_t smem_u32(const void* p) { return (uint32_t)__cvta_generic_to_shared(p); }

__device__ __forceinline__ void mbar_init(uint32_t a, uint32_t c) {
    asm volatile("mbarrier.init.shared.b64 [%0], %1;" :: "r"(a), "r"(c) : "memory");
}
__device__ __forceinline__ void mbar_expect_tx(uint32_t a, uint32_t bytes) {
    asm volatile("mbarrier.arrive.expect_tx.shared.b64 _, [%0], %1;" :: "r"(a), "r"(bytes) : "memory");
}
__device__ __forceinline__ void mbar_arrive(uint32_t a) {
    asm volatile("mbarrier.arrive.shared.b64 _, [%0];" :: "r"(a) : "memory");
}
__device__ __forceinline__ void mbar_arrive2(uint32_t a) {
    asm volatile("mbarrier.arrive.shared.b64 _, [%0], 2;" :: "r"(a) : "memory");
}
__device__ __forceinline__ bool mbar_test(uint32_t a, uint32_t parity) {
    uint32_t ok;
    asm volatile("{\n.reg .pred p;\nmbarrier.test_wait.parity.shared.b64 p, [%1], %2;\nselp.u32 %0, 1, 0, p;\n}"
                 : "=r"(ok) : "r"(a), "r"(parity) : "memory");
    return ok;
}
__device__ __forceinline__ uint32_t clock32() {
    uint32_t c;
    asm volatile("mov.u32 %0, %%clock;" : "=r"(c));
    return c;
}
__device__ __forceinline__ void mbar_wait(uint32_t a, uint32_t parity) {
    uint32_t ok;
    int it = 0;
    do {
        asm volatile("{\n.reg .pred p;\nmbarrier.try_wait.parity.shared.b64 p, [%1], %2;\nselp.u32 %0, 1, 0, p;\n}"
                     : "=r"(ok) : "r"(a), "r"(parity) : "memory");
    } while (!ok && ++it < SPIN_MAX);
}
__device__ __forceinline__ void tma_tile(uint32_t dst, const CUtensorMap* tm, int group, uint32_t bar, uint64_t pol) {
    asm volatile("cp.async.bulk.tensor.4d.shared::cluster.global.mbarrier::complete_tx::bytes.L2::cache_hint"
                 " [%0], [%1, {%3, %3, %3, %4}], [%2], %5;"
                 :: "r"(dst), "l"(tm), "r"(bar), "r"(0), "r"(group), "l"(pol) : "memory");
}
__device__ __forceinline__ void tma_2d(uint32_t dst, const CUtensorMap* tm, int c0, int c1, uint32_t bar) {
    asm volatile("cp.async.bulk.tensor.2d.shared::cluster.global.mbarrier::complete_tx::bytes [%0], [%1, {%3, %4}], [%2];"
                 :: "r"(dst), "l"(tm), "r"(bar), "r"(c0), "r"(c1) : "memory");
}
__device__ __forceinline__ void cbar() { asm volatile("bar.sync 1, 256;" ::: "memory"); }

__device__ __forceinline__ uint4 lds128(uint32_t a) {
    uint4 v;
    asm volatile("ld.shared.v4.u32 {%0,%1,%2,%3}, [%4];" : "=r"(v.x), "=r"(v.y), "=r"(v.z), "=r"(v.w) : "r"(a) : "memory");
    return v;
}
__device__ __forceinline__ uint4 ldm4(uint32_t a) {
    uint4 v;
    asm volatile("ldmatrix.sync.aligned.m8n8.x4.shared.b16 {%0,%1,%2,%3}, [%4];"
                 : "=r"(v.x), "=r"(v.y), "=r"(v.z), "=r"(v.w) : "r"(a) : "memory");
    return v;
}
__device__ __forceinline__ uint4 ldm4t(uint32_t a) {
    uint4 v;
    asm volatile("ldmatrix.sync.aligned.m8n8.x4.trans.shared.b16 {%0,%1,%2,%3}, [%4];"
                 : "=r"(v.x), "=r"(v.y), "=r"(v.z), "=r"(v.w) : "r"(a) : "memory");
    return v;
}
__device__ __forceinline__ void mma16816(float (&c)[4], uint32_t a0, uint32_t a1, uint32_t a2, uint32_t a3, uint32_t b0, uint32_t b1) {
    asm volatile("mma.sync.aligned.m16n8k16.row.col.f32.bf16.bf16.f32 {%0,%1,%2,%3}, {%4,%5,%6,%7}, {%8,%9}, {%0,%1,%2,%3};"
                 : "+f"(c[0]), "+f"(c[1]), "+f"(c[2]), "+f"(c[3])
                 : "r"(a0), "r"(a1), "r"(a2), "r"(a3), "r"(b0), "r"(b1));
}
__device__ __forceinline__ uint4 ld_rlx128(const uint32_t* p) {
    uint4 v;
    asm volatile("ld.relaxed.gpu.global.v4.u32 {%0,%1,%2,%3}, [%4];" : "=r"(v.x), "=r"(v.y), "=r"(v.z), "=r"(v.w) : "l"(p) : "memory");
    return v;
}
__device__ __forceinline__ void ld_rlx128_if(bool c, uint4& v, const uint32_t* p) {
    asm volatile("{\n.reg .pred p;\nsetp.ne.u32 p, %5, 0;\n@p ld.relaxed.gpu.global.v4.u32 {%0,%1,%2,%3}, [%4];\n}"
                 : "+r"(v.x), "+r"(v.y), "+r"(v.z), "+r"(v.w) : "l"(p), "r"((uint32_t)c) : "memory");
}
__device__ __forceinline__ uint32_t ldg32_now(const void* p) {
    uint32_t v;
    asm volatile("ld.global.nc.u32 %0, [%1];" : "=r"(v) : "l"(p) : "memory");
    return v;
}
__device__ __forceinline__ uint4 ldg128_now(const void* p) {
    uint4 v;
    asm volatile("ld.global.nc.v4.u32 {%0,%1,%2,%3}, [%4];" : "=r"(v.x), "=r"(v.y), "=r"(v.z), "=r"(v.w) : "l"(p) : "memory");
    return v;
}
__device__ __forceinline__ void st_rlx32(uint32_t* p, uint32_t v) {
    asm volatile("st.relaxed.gpu.global.u32 [%0], %1;" :: "l"(p), "r"(v) : "memory");
}
__device__ __forceinline__ void st_rlx64(uint32_t* p, uint32_t a, uint32_t b) {
    asm volatile("st.relaxed.gpu.global.v2.u32 [%0], {%1,%2};" :: "l"(p), "r"(a), "r"(b) : "memory");
}

__device__ __forceinline__ void st_rlx64_if(bool c, uint32_t* p, uint32_t a, uint32_t b) {
    asm volatile("{\n.reg .pred p;\nsetp.ne.u32 p, %3, 0;\n@p st.relaxed.gpu.global.v2.u32 [%0], {%1,%2};\n}"
                 :: "l"(p), "r"(a), "r"(b), "r"((uint32_t)c) : "memory");
}

__device__ __forceinline__ void st_rlx128_if(bool c, uint32_t* p, uint32_t a, uint32_t b, uint32_t d, uint32_t e) {
    asm volatile("{\n.reg .pred p;\nsetp.ne.u32 p, %5, 0;\n@p st.relaxed.gpu.global.v4.u32 [%0], {%1,%2,%3,%4};\n}"
                 :: "l"(p), "r"(a), "r"(b), "r"(d), "r"(e), "r"((uint32_t)c) : "memory");
}
__device__ __forceinline__ float bf_lo(uint32_t w) { return __uint_as_float(w << 16); }
__device__ __forceinline__ float bf_hi(uint32_t w) { return __uint_as_float(w & 0xffff0000u); }
__device__ __forceinline__ uint32_t pack_bf(float lo, float hi) {
    __nv_bfloat162 v = __floats2bfloat162_rn(lo, hi);
    return *reinterpret_cast<uint32_t*>(&v);
}
__device__ __forceinline__ float rbf(float x) { return __uint_as_float(pack_bf(0.f, x)); }
__device__ __forceinline__ uint32_t enc(uint32_t w) { return w ? w : 0x80008000u; }

__device__ __forceinline__ float warp_sum(float v) {
#pragma unroll
    for (int o = 16; o > 0; o >>= 1) v += __shfl_xor_sync(0xffffffffu, v, o);
    return v;
}

__device__ __forceinline__ void layernorm_row(const uint4& r0, const uint4& r1, int lane, uint32_t dst_row) {
    const bool act = lane < 28;
    float v[16];
    const uint32_t w[8] = {r0.x, r0.y, r0.z, r0.w, r1.x, r1.y, r1.z, r1.w};
#pragma unroll
    for (int i = 0; i < 8; i++) { v[2 * i] = act ? bf_lo(w[i]) : 0.f; v[2 * i + 1] = act ? bf_hi(w[i]) : 0.f; }
    float s = 0.f;
#pragma unroll
    for (int i = 0; i < 16; i++) s += v[i];
    const float mean = warp_sum(s) * (1.0f / DM);
    float q = 0.f;
#pragma unroll
    for (int i = 0; i < 16; i++) { const float d = v[i] - mean; q = fmaf(d, d, q); }
    const float var = warp_sum(act ? q : 0.f) * (1.0f / DM);
    const float mb = rbf(mean);
    const float sd = rbf(sqrtf(rbf(rbf(var) + 1e-5f)));
    const float rs = 1.0f / sd;
    uint32_t o[8];
#pragma unroll
    for (int i = 0; i < 8; i++) o[i] = pack_bf(rbf(v[2 * i] - mb) * rs, rbf(v[2 * i + 1] - mb) * rs);
    if (act) {
        asm volatile("st.shared.v4.u32 [%0], {%1,%2,%3,%4};" :: "r"(dst_row + lane * 16), "r"(o[0]), "r"(o[1]), "r"(o[2]), "r"(o[3]) : "memory");
        asm volatile("st.shared.v4.u32 [%0], {%1,%2,%3,%4};" :: "r"(dst_row + 448 + lane * 16), "r"(o[4]), "r"(o[5]), "r"(o[6]), "r"(o[7]) : "memory");
    }
}

template <class T> __device__ __forceinline__ T* pin(T* p) { asm volatile("" : "+l"(p)); return p; }
__device__ __forceinline__ uint32_t pin(uint32_t v) { asm volatile("" : "+r"(v)); return v; }
__device__ __forceinline__ void sts64(uint32_t a, float x, float y) {
    asm volatile("st.shared.v2.f32 [%0], {%1,%2};" :: "r"(a), "f"(x), "f"(y) : "memory");
}
__device__ __forceinline__ void sts128(uint32_t a, float x, float y, float z, float w) {
    asm volatile("st.shared.v4.f32 [%0], {%1,%2,%3,%4};" :: "r"(a), "f"(x), "f"(y), "f"(z), "f"(w) : "memory");
}
__device__ __forceinline__ float2 lds64f(uint32_t a) {
    float2 v;
    asm volatile("ld.shared.v2.f32 {%0,%1}, [%2];" : "=f"(v.x), "=f"(v.y) : "r"(a) : "memory");
    return v;
}
__device__ __forceinline__ float4 lds128f(uint32_t a) {
    float4 v;
    asm volatile("ld.shared.v4.f32 {%0,%1,%2,%3}, [%4];" : "=f"(v.x), "=f"(v.y), "=f"(v.z), "=f"(v.w) : "r"(a) : "memory");
    return v;
}
__device__ __forceinline__ uint32_t add_bf2(uint32_t a, uint32_t b) {
    uint32_t d;
    asm("add.rn.bf16x2 %0, %1, %2;" : "=r"(d) : "r"(a), "r"(b));
    return d;
}
__device__ __forceinline__ uint32_t neg_sq_relu_bf2(uint32_t a) {
    uint32_t d;
    asm("{\n.reg .b32 r, n;\nmax.bf16x2 r, %1, %2;\nneg.bf16x2 n, r;\nmul.rn.bf16x2 %0, r, n;\n}" : "=r"(d) : "r"(a), "r"(0));
    return d;
}

#define V4(v) "+r"(v.x), "+r"(v.y), "+r"(v.z), "+r"(v.w)
#define POLL_HEAD(label) "mov.u32 it, 0;\n" label ":\nadd.u32 it, it, 1;\nsetp.lt.u32 c, it, 4194304;\n"
#define POLL_EXIT(label) "and.pred q, q, c;\nvote.sync.any.pred q, q, 0xffffffff;\n@!q bra " label "_END;\n"
#define POLL_LD(p, regs, addr) "@" p " ld.relaxed.gpu.global.v4.u32 {" regs "}, [" addr "];\n"
__device__ __forceinline__ void poll_nz(uint4& v, const uint32_t* p) {
    asm volatile("{\n.reg .pred p0, q, c;\n.reg .b32 t, it;\n" POLL_HEAD("PA")
                 "min.u32 t, %0, %1;\nmin.u32 t, t, %2;\nmin.u32 t, t, %3;\nsetp.eq.u32 p0, t, 0;\nmov.pred q, p0;\n"
                 POLL_EXIT("PA") POLL_LD("p0", "%0,%1,%2,%3", "%4") "bra PA;\nPA_END:\n}"
                 : V4(v) : "l"(p) : "memory");
}
__device__ __forceinline__ void poll_nz2(uint4& v, uint4& w, const uint32_t* p) {
    asm volatile("{\n.reg .pred p0, p1, q, c;\n.reg .b32 t, u, it;\n" POLL_HEAD("PB")
                 "min.u32 t, %0, %1;\nmin.u32 t, t, %2;\nmin.u32 t, t, %3;\nsetp.eq.u32 p0, t, 0;\n"
                 "min.u32 u, %4, %5;\nmin.u32 u, u, %6;\nmin.u32 u, u, %7;\nsetp.eq.u32 p1, u, 0;\nor.pred q, p0, p1;\n"
                 POLL_EXIT("PB") POLL_LD("p0", "%0,%1,%2,%3", "%8") POLL_LD("p1", "%4,%5,%6,%7", "%8+512") "bra PB;\nPB_END:\n}"
                 : V4(v), V4(w) : "l"(p) : "memory");
}
__device__ __forceinline__ void poll_nz_pair(uint32_t& v, uint32_t& w, const uint32_t* p) {
    asm volatile("{\n.reg .pred q, c;\n.reg .b32 t, it;\n" POLL_HEAD("PC")
                 "ld.relaxed.gpu.global.u32 %0, [%2];\nld.relaxed.gpu.global.u32 %1, [%2+64];\n"
                 "min.u32 t, %0, %1;\nsetp.eq.u32 q, t, 0;\n"
                 POLL_EXIT("PC") "bra PC;\nPC_END:\n}"
                 : "=&r"(v), "=&r"(w) : "l"(p) : "memory");
}
__device__ __forceinline__ void poll_tag4(uint4& a, uint4& b, uint4& c, uint4& d, const uint32_t* p, uint32_t tag) {
    asm volatile("{\n.reg .pred p0, p1, p2, p3, q, c;\n.reg .b32 t, u, it;\n" POLL_HEAD("PD")
                 "lop3.b32 t, %0, %1, %17, 0x7e;\nlop3.b32 u, %2, %3, %17, 0x7e;\nlop3.b32 t, t, u, 1, 0xa8;\nsetp.ne.u32 p0, t, 0;\n"
                 "lop3.b32 t, %4, %5, %17, 0x7e;\nlop3.b32 u, %6, %7, %17, 0x7e;\nlop3.b32 t, t, u, 1, 0xa8;\nsetp.ne.u32 p1, t, 0;\n"
                 "lop3.b32 t, %8, %9, %17, 0x7e;\nlop3.b32 u, %10, %11, %17, 0x7e;\nlop3.b32 t, t, u, 1, 0xa8;\nsetp.ne.u32 p2, t, 0;\n"
                 "lop3.b32 t, %12, %13, %17, 0x7e;\nlop3.b32 u, %14, %15, %17, 0x7e;\nlop3.b32 t, t, u, 1, 0xa8;\nsetp.ne.u32 p3, t, 0;\n"
                 "or.pred q, p0, p1;\nor.pred q, q, p2;\nor.pred q, q, p3;\n"
                 POLL_EXIT("PD") POLL_LD("p0", "%0,%1,%2,%3", "%16") POLL_LD("p1", "%4,%5,%6,%7", "%16+512")
                 POLL_LD("p2", "%8,%9,%10,%11", "%16+1024") POLL_LD("p3", "%12,%13,%14,%15", "%16+1536") "bra PD;\nPD_END:\n}"
                 : V4(a), V4(b), V4(c), V4(d) : "l"(p), "r"(tag) : "memory");
}
__device__ __forceinline__ void poll_sign4(uint4& a, uint4& b, uint4& c, uint4& d, const uint32_t* p) {
    asm volatile("{\n.reg .pred p0, p1, p2, p3, q, c;\n.reg .b32 t, it;\n" POLL_HEAD("PE")
                 "lop3.b32 t, %0, %1, %2, 0x80;\nlop3.b32 t, t, %3, 0x80000000, 0x2a;\nsetp.ne.u32 p0, t, 0;\n"
                 "lop3.b32 t, %4, %5, %6, 0x80;\nlop3.b32 t, t, %7, 0x80000000, 0x2a;\nsetp.ne.u32 p1, t, 0;\n"
                 "lop3.b32 t, %8, %9, %10, 0x80;\nlop3.b32 t, t, %11, 0x80000000, 0x2a;\nsetp.ne.u32 p2, t, 0;\n"
                 "lop3.b32 t, %12, %13, %14, 0x80;\nlop3.b32 t, t, %15, 0x80000000, 0x2a;\nsetp.ne.u32 p3, t, 0;\n"
                 "or.pred q, p0, p1;\nor.pred q, q, p2;\nor.pred q, q, p3;\n"
                 POLL_EXIT("PE") POLL_LD("p0", "%0,%1,%2,%3", "%16") POLL_LD("p1", "%4,%5,%6,%7", "%16+256")
                 POLL_LD("p2", "%8,%9,%10,%11", "%16+512") POLL_LD("p3", "%12,%13,%14,%15", "%16+768") "bra PE;\nPE_END:\n}"
                 : V4(a), V4(b), V4(c), V4(d) : "l"(p) : "memory");
}

constexpr uint32_t ONES = 0x3f803f80u;

__device__ __forceinline__ void ffn1_finish(uint32_t bar, uint32_t a_w1, uint32_t a_part, uint32_t a_stat,
                                            uint32_t bias_a, uint32_t bias_b, uint32_t* dst) {
    float w0[4] = {}, w1[4] = {}, w2[4] = {}, w3[4] = {};
    mbar_wait(bar, 0);
#pragma unroll 1
    for (int s = 0; s < 28; s += 14) {
        uint4 bw[14];
#pragma unroll
        for (int i = 0; i < 14; i++) bw[i] = ldm4t(a_w1 + (s + i) * 1024);
#pragma unroll
        for (int i = 0; i < 14; i += 2) {
            mma16816(w0, ONES, ONES, ONES, ONES, bw[i].x, bw[i].y);
            mma16816(w1, ONES, ONES, ONES, ONES, bw[i].z, bw[i].w);
            mma16816(w2, ONES, ONES, ONES, ONES, bw[i + 1].x, bw[i + 1].y);
            mma16816(w3, ONES, ONES, ONES, ONES, bw[i + 1].z, bw[i + 1].w);
        }
    }
    const float cs0 = w0[0] + w2[0], cs1 = w0[1] + w2[1], cs2 = w1[0] + w3[0], cs3 = w1[1] + w3[1];
    asm volatile("bar.sync 2, 288;" ::: "memory");
    float2 sq[7];
    float4 p[7];
#pragma unroll
    for (int w = 0; w < 7; w++) sq[w] = lds64f(a_stat + w * 64);
#pragma unroll
    for (int w = 0; w < 7; w++) p[w] = lds128f(a_part + w * 1024);
    const float mean = (((sq[0].x + sq[1].x) + (sq[2].x + sq[3].x)) + ((sq[4].x + sq[5].x) + sq[6].x)) * (1.0f / DM);
    const float msq = (((sq[0].y + sq[1].y) + (sq[2].y + sq[3].y)) + ((sq[4].y + sq[5].y) + sq[6].y)) * (1.0f / DM);
    const float var = fmaxf(fmaf(-mean, mean, msq), 0.f);
    float sd, rs;
    asm("sqrt.approx.ftz.f32 %0, %1;" : "=f"(sd) : "f"(rbf(rbf(var) + 1e-5f)));
    asm("rcp.approx.ftz.f32 %0, %1;" : "=f"(rs) : "f"(rbf(sd)));
    const float mb = rbf(mean);
    const float s0 = fmaf(-mb, cs0, ((p[0].x + p[1].x) + (p[2].x + p[3].x)) + ((p[4].x + p[5].x) + p[6].x));
    const float s1 = fmaf(-mb, cs1, ((p[0].y + p[1].y) + (p[2].y + p[3].y)) + ((p[4].y + p[5].y) + p[6].y));
    const float s2 = fmaf(-mb, cs2, ((p[0].z + p[1].z) + (p[2].z + p[3].z)) + ((p[4].z + p[5].z) + p[6].z));
    const float s3 = fmaf(-mb, cs3, ((p[0].w + p[1].w) + (p[2].w + p[3].w)) + ((p[4].w + p[5].w) + p[6].w));
    st_rlx64(dst, neg_sq_relu_bf2(add_bf2(pack_bf(s0 * rs, s1 * rs), bias_a)),
             neg_sq_relu_bf2(add_bf2(pack_bf(s2 * rs, s3 * rs), bias_b)));
}

__global__ void __launch_bounds__(NTHREADS, 1)
fused_decode_kernel(const __nv_bfloat16* __restrict__ x, const __nv_bfloat16* __restrict__ wq,
                    const __nv_bfloat16* __restrict__ b1, const __nv_bfloat16* __restrict__ b2,
                    __nv_bfloat16* __restrict__ out,
                    const __grid_constant__ CUtensorMap tm_k, const __grid_constant__ CUtensorMap tm_v,
                    const __grid_constant__ CUtensorMap tm_wo, const __grid_constant__ CUtensorMap tm_w1,
                    const __grid_constant__ CUtensorMap tm_w2) {
    extern __shared__ __align__(1024) uint8_t sp[];
    const uint32_t sb = pin(smem_u32(sp));

    const int tid = threadIdx.x, warp = tid >> 5, lane = tid & 31;
    const int g = lane >> 2, t4 = lane & 3;
    const int cta = blockIdx.x;
    CKDECL;
    const int hd = cta >> 3, bj = cta & 7;
    const bool tail = bj < 7;
    const int ri = (hd * 7 + bj) >> 1;
    const bool ffn2 = (hd + bj) & 1;
    const int bg = ri & 1, cg = ri >> 1;
    const uint32_t bar_full = sb + OFF_BAR, bar_empty = bar_full + NS * 8, bar_w = bar_empty + NS * 8;
    const uint32_t s_wq = sb + OFF_WO, s_est = sb + OFF_M + 64;

    uint32_t epoch;
    asm volatile("ld.relaxed.gpu.global.u32 %0, [%1];" : "=r"(epoch) : "l"(g_epoch[cta]) : "memory");
    uint4 xr0 = make_uint4(0, 0, 0, 0), xr1 = xr0;
    if (warp < 8) {
        if (lane < 28) {
            xr0 = ldg128_now(x + warp * DM + lane * 8);
            xr1 = ldg128_now(x + warp * DM + 224 + lane * 8);
        }
        const int row = tid >> 2, ch = tid & 3;
        const uint32_t d = s_wq + row * 64 + ((ch ^ ((row >> 1) & 3)) << 4);
        const __nv_bfloat16* p = wq + (size_t)row * (NH * DH) + cta * 32 + ch * 8;
#pragma unroll
        for (int i = 0; i < 7; i++)
            asm volatile("cp.async.cg.shared.global.L2::128B [%0], [%1], 16;"
                         :: "r"(d + i * 4096), "l"(p + (size_t)i * 64 * (NH * DH)) : "memory");
    }
    const int grp0 = (bj * NH + hd) * (SK / 8), flip = (hd & 1) * (KT / 2);
    uint64_t pol;
    asm volatile("createpolicy.fractional.L2::evict_first.b64 %0, 1.0;" : "=l"(pol));
    PROF(tid == 288, 0);
    if (tid == 256) {
#pragma unroll
        for (int s = 0; s < D0; s++) mbar_init(bar_full + s * 8, 1);
        asm volatile("fence.mbarrier_init.release.cluster;" ::: "memory");
#pragma unroll
        for (int s = 0; s < D0; s++) {
            mbar_expect_tx(bar_full + s * 8, STAGE);
            tma_tile(sb + OFF_RING + s * STAGE, &tm_k, grp0 + (s ^ flip) * 4, bar_full + s * 8, pol);
        }
    }

    if (warp == 8) {
        if (lane == 0) {
#pragma unroll
            for (int s = D0; s < NS; s++) mbar_init(bar_full + s * 8, 1);
#pragma unroll
            for (int s = 0; s < NS; s++) mbar_init(bar_empty + s * 8, 8);
#pragma unroll
            for (int s = 0; s < 9; s++) mbar_init(bar_w + s * 8, s == 1 ? 8 : 1);
            asm volatile("fence.mbarrier_init.release.cluster;" ::: "memory");
            asm volatile("st.volatile.shared.v2.u32 [%0], {%1,%2};" :: "r"(s_est), "r"(0), "r"(clock32()) : "memory");
        }
        __syncwarp();
        asm volatile("bar.arrive 3, 288;" ::: "memory");
        asm volatile("bar.arrive 7, 64;" ::: "memory");
        if (lane != 0) return;
        asm volatile("prefetch.tensormap [%0];" :: "l"(&tm_v) : "memory");
        asm volatile("prefetch.tensormap [%0];" :: "l"(&tm_wo) : "memory");
        asm volatile("prefetch.tensormap [%0];" :: "l"(ffn2 ? &tm_w2 : &tm_w1) : "memory");
        uint32_t* prog = g_prog[(epoch + 1) & 1];
        uint32_t t = D0, landed = 0;
#pragma unroll 1
        for (int it = 0; t < NT && it < 16 * SPIN_MAX; it++) {
            if (landed < t && mbar_test(bar_full + (landed & (NS - 1)) * 8, (landed / NS) & 1)) {
                landed++;
                if (((landed + cta) & 3) == 0) asm volatile("red.relaxed.gpu.global.add.u32 [%0], 4;" :: "l"(prog) : "memory");
            }
            const uint32_t s = t & (NS - 1);
            if (t < NS) {
                if (t - landed >= D0) continue;
            } else {
                if (t - landed >= NS) continue;
                if (t - landed >= 2) {
                    uint32_t v, c0;
                    asm volatile("ld.volatile.shared.v2.u32 {%0,%1}, [%2];" : "=r"(v), "=r"(c0) : "r"(s_est) : "memory");
                    if (t * NCTA > v + min(((clock32() - c0) * 7) >> 6, 256u) + (t - landed > 2 ? WIN : WIN + EXTRA)) continue;
                }
                if (!mbar_test(bar_empty + s * 8, (t / NS - 1) & 1)) continue;
            }
            mbar_expect_tx(bar_full + s * 8, STAGE);
            tma_tile(sb + OFF_RING + s * STAGE, t < KT ? &tm_k : &tm_v, grp0 + ((t ^ flip) & (KT - 1)) * 4, bar_full + s * 8, pol);
            t++;
        }
        asm volatile("red.relaxed.gpu.global.add.u32 [%0], %1;" :: "l"(prog), "r"(NT - ((landed + (cta & 3)) & ~3u)) : "memory");
        if (!tail) return;
        mbar_wait(bar_full + ((NT - 1 - XO) & (NS - 1)) * 8, ((NT - 1 - XO) / NS) & 1);
        mbar_expect_tx(bar_w, DH * 128);
        tma_2d(sb + OFF_WO, &tm_wo, bj * 64, hd * DH, bar_w);
        if (!ffn2) {
            mbar_wait(bar_full + ((NT - 1 - X1) & (NS - 1)) * 8, ((NT - 1 - X1) / NS) & 1);
            mbar_expect_tx(bar_w + 16, DM * 64);
            tma_2d(sb + OFF_W, &tm_w1, ri * 32, 0, bar_w + 16);
            tma_2d(sb + OFF_W + 224 * 64, &tm_w1, ri * 32, 224, bar_w + 16);
        } else {
            mbar_wait(bar_w + 8, 0);
#pragma unroll
            for (int i = 0; i < 7; i++) {
                mbar_expect_tx(bar_w + (2 + i) * 8, 8192);
                tma_2d(sb + OFF_RING + i * 8192, &tm_w2, cg * 16, i * 256, bar_w + (2 + i) * 8);
            }
        }
        return;
    }

    const uint32_t par = (epoch + 1) & 1;
    const uint32_t a_w1 = pin(sb + OFF_W + (((lane >> 3) & 1) * 8 + (lane & 7)) * 64 + (((lane >> 4) ^ ((lane >> 1) & 3)) << 4));
    const uint32_t a_stat = pin(sb + OFF_B + 7168 + g * 8);

    if (warp == 9) {
        uint32_t bias_a = 0, bias_b = 0;
        if (tail && !ffn2) {
            bias_a = ldg32_now(b1 + ri * 32 + 16 + t4 * 2);
            bias_b = ldg32_now(b1 + ri * 32 + 24 + t4 * 2);
        }
        uint4 q = make_uint4(0, 0, 0, 0);
        poll_nz(q, &g_q[par][bj * (NH * DH / 2) + hd * (DH / 2) + lane * 4]);
        *reinterpret_cast<uint4*>(sp + OFF_Q + lane * 16) = q;
        asm volatile("bar.arrive 5, 288;" ::: "memory");
        asm volatile("bar.sync 7, 64;" ::: "memory");
        if (lane == 0) {
            uint32_t v = 0;
#pragma unroll 1
            for (int it = 0; v + WIN < (NT - 1) * NCTA && it < SPIN_MAX; it++) {
                asm volatile("ld.relaxed.gpu.global.u32 %0, [%1];" : "=r"(v) : "l"(g_prog[par]) : "memory");
                asm volatile("st.volatile.shared.v2.u32 [%0], {%1,%2};" :: "r"(s_est), "r"(v), "r"(clock32()) : "memory");
                __nanosleep(HSLEEP);
            }
        }
        __syncwarp();
        if (tail && !ffn2) {
            ffn1_finish(bar_w + 16, a_w1 ^ 32, pin(sb + OFF_B + 512 + lane * 16), a_stat, bias_a, bias_b,
                        pin(&g_g[par][((g >> 2) * NMSG + ri * 2 + 1) * 32 + (g & 3) * 8 + (t4 ^ 1) * 2]));
            CK32(8);
            CKOUT();
        }
        return;
    }

    asm volatile("cp.async.commit_group;" ::: "memory");
    uint32_t c0w = 0, c1w = 0;
    if (!tail) {
        if (warp < 7) {
            const __nv_bfloat16* p = x + (hd >> 1) * DM + warp * 64 + (hd & 1) * 32 + ((lane >> 2) & 1) * 16 + t4 * 2;
            c0w = ldg32_now(p);
            c1w = ldg32_now(p + 8);
        }
    } else if (warp == 7) {
        if (ffn2) {
            c0w = ldg32_now(b2 + cg * 16 + (lane & 1) * 8 + (g & 6));
            c0w = __byte_perm(c0w, 0, (g & 1) ? 0x3232 : 0x1010);
        } else {
            c0w = ldg32_now(b1 + ri * 32 + t4 * 2);
            c1w = ldg32_now(b1 + ri * 32 + 8 + t4 * 2);
        }
    }

    layernorm_row(xr0, xr1, lane, sb + OFF_C + warp * (XP * 2));
    asm volatile("cp.async.wait_group 0;" ::: "memory");
    asm volatile("bar.sync 3, 288;" ::: "memory");

    float* red_b = reinterpret_cast<float*>(sp + OFF_B);
    if (warp < 7) {
        float acc[4][4] = {};
#pragma unroll
        for (int p = 0; p < 2; p++) {
            const uint4 a = ldm4(sb + OFF_C + (lane & 7) * (XP * 2) + (warp * 64 + p * 32 + (lane >> 3) * 8) * 2);
#pragma unroll
            for (int s = 0; s < 2; s++) {
                const int row = warp * 64 + p * 32 + s * 16 + ((lane >> 3) & 1) * 8 + (lane & 7);
#pragma unroll
                for (int np = 0; np < 2; np++) {
                    const int ch = np * 2 + (lane >> 4);
                    const uint4 bw = ldm4t(s_wq + row * 64 + ((ch ^ ((row >> 1) & 3)) << 4));
                    mma16816(acc[np * 2], s ? a.z : a.x, 0, s ? a.w : a.y, 0, bw.x, bw.y);
                    mma16816(acc[np * 2 + 1], s ? a.z : a.x, 0, s ? a.w : a.y, 0, bw.z, bw.w);
                }
            }
        }
#pragma unroll
        for (int n = 0; n < 4; n++)
            *reinterpret_cast<float2*>(red_b + (warp * 8 + g) * 40 + n * 8 + t4 * 2) = make_float2(acc[n][0], acc[n][1]);
    }
    asm volatile("fence.proxy.async.shared::cta;" ::: "memory");
    cbar();
    if (tid < 128) {
        const int b = tid >> 4, wd = tid & 15;
        float s0 = 0.f, s1 = 0.f;
#pragma unroll
        for (int w = 0; w < 7; w++) {
            const float2 p = *reinterpret_cast<const float2*>(red_b + (w * 8 + b) * 40 + wd * 2);
            s0 += p.x; s1 += p.y;
        }
        st_rlx32(&g_q[par][b * (NH * DH / 2) + cta * 16 + (wd & 3) * 4 + ((wd >> 2) & 1) * 2 + (wd >> 3)], enc(pack_bf(s0, s1)));
    } else {
        const int i = tid - 128;
        g_q[par ^ 1][cta * 128 + i] = 0;
        g_o[par ^ 1][cta * 128 + i] = 0;
        if (i < 56) g_g[par ^ 1][cta * 56 + i] = 0;
        if (i < 14 * HREP) (&g_h[0][0][0])[((par ^ 1) * NCTA + cta) * (14 * HREP) + i] = 0;
        if (cta == 0 && i == 0) g_prog[par ^ 1][0] = 0;
    }
    PROF(tid == 0, 1);

    uint32_t* const p_o_st = pin(&g_o[par][(hd * 8 + warp) * 128 + bj * 16 + t4 * 4]);
    const uint32_t* const p_o_ld = pin(&g_o[par][(hd * 8 + warp) * 128 + lane * 4]);
    uint32_t* const p_p2_st = pin(g_p2 + ((bj * 16 + warp * 2 + (lane >> 4)) * 16 + hd) * 32 + (lane & 15) * 2);
    const uint32_t* p_in;
    uint32_t* p_res;
    if (!tail) {
        p_in = g_p2 + ((warp * 16 + hd) * 16 + (lane >> 3)) * 32 + (lane & 7) * 4;
        p_res = &g_h[par][(lane >> 3) % HREP][(warp * 2 + (hd & 1)) * 128 + (hd >> 1) * 16 + t4 * 4 + ((lane >> 2) & 1) * 2];
    } else if (!ffn2) {
        p_in = &g_h[par][ri % HREP][warp * 256 + lane * 4];
        p_res = &g_g[par][((g >> 2) * NMSG + ri * 2) * 32 + (g & 3) * 8 + t4 * 2];
    } else {
        const int b = bg * 4 + (lane & 2);
        p_in = warp < 7 ? &g_g[par][(bg * NMSG + warp * 16 + (g >> 2) * 8 + (t4 >> 1)) * 32 + (g & 3) * 8 + (t4 & 1) * 4]
                        : &g_h[par][ri % HREP][(cg >> 1) * 128 + b * 16 + (g >> 1) * 4 + (cg & 1) * 2 + (lane & 1)];
        p_res = reinterpret_cast<uint32_t*>(out + b * DM + cg * 16 + (lane & 1) * 8 + g);
    }
    p_in = pin(p_in);
    p_res = pin(p_res);
    constexpr int RED_TILE = NT - 3;
    const uint32_t a_wo = pin(sb + OFF_WO + (warp * 32 + (lane >> 4) * 8 + (lane & 7)) * 128 + ((((lane >> 3) & 1) ^ (lane & 7)) << 4));
    const uint32_t a_r2w = pin(sb + OFF_RING + (RED_TILE % NS) * STAGE + warp * 2048 + (t4 * 8 + ((g + 2 * t4) & 7)) * 16);
    const uint32_t a_r2r = pin(sb + OFF_RING + (RED_TILE % NS) * STAGE + (lane >> 3) * 512 +
                               ((warp >> 1) * 8 + ((lane + (warp & 6)) & 7)) * 16 + ((warp ^ (lane >> 3)) & 1) * 8);
    __nv_bfloat16* sc = reinterpret_cast<__nv_bfloat16*>(sp + OFF_A);

    float mx = -INFINITY;
    {
        uint4 q[8];
        asm volatile("bar.sync 5, 288;" ::: "memory");
#pragma unroll
        for (int i = 0; i < 8; i++) q[i] = lds128(sb + OFF_Q + i * 64 + t4 * 16);
        PROF(tid == 0, 2);
        const uint32_t ka = pin(sb + OFF_RING + (warp & 3) * 4096 + (lane & 7) * 128 + (((lane >> 3) ^ (lane & 7)) << 4));
        uint32_t* scw = reinterpret_cast<uint32_t*>(sc) + t4 * 4 + (warp & 1) * 2 + ((warp >> 1) & 1);
#pragma unroll 1
        for (int t = warp >> 2; t < KT; t += 2) {
            const int st = t & (NS - 1);
            mbar_wait(bar_full + st * 8, (t / NS) & 1);
            uint4 kf[8];
#pragma unroll
            for (int i = 0; i < 8; i++) kf[i] = ldm4((ka ^ ((i & 1) << 6)) + st * STAGE + (i >> 1) * 1024);
            float c[4][4] = {};
#pragma unroll
            for (int i = 0; i < 8; i++) {
                mma16816(c[(i & 1) * 2], q[i].x, q[i].y, q[i].z, q[i].w, kf[i].x, kf[i].y);
                mma16816(c[(i & 1) * 2 + 1], q[i].x, q[i].y, q[i].z, q[i].w, kf[i].z, kf[i].w);
            }
            if (lane == 0) mbar_arrive2(bar_empty + st * 8);
            const uint32_t d = pack_bf((c[0][0] + c[2][0]) + (c[1][2] + c[3][2]), (c[0][1] + c[2][1]) + (c[1][3] + c[3][3]));
            const uint32_t sw = pack_bf(bf_lo(d) * 0.0625f, bf_hi(d) * 0.0625f);
            mx = fmaxf(mx, fmaxf(bf_lo(sw), bf_hi(sw)));
            if (lane < 4) scw[t * 16] = sw;
        }
    }
    PROF(tid == 0, 3);

    {
        float* sm_m = reinterpret_cast<float*>(sp + OFF_M);
        mx = fmaxf(mx, __shfl_xor_sync(0xffffffffu, mx, 1));
        mx = fmaxf(mx, __shfl_xor_sync(0xffffffffu, mx, 2));
        if (lane == 0) sm_m[warp] = mx;
        cbar();
#pragma unroll
        for (int w = 0; w < 8; w++) mx = fmaxf(mx, sm_m[w]);
        float e[16], sum = 0.f;
#pragma unroll
        for (int i = 0; i < 4; i++) {
            const uint2 s = *reinterpret_cast<const uint2*>(sc + i * 1024 + tid * 4);
            e[i * 4 + 0] = expf(bf_lo(s.x) - mx); e[i * 4 + 1] = expf(bf_hi(s.x) - mx);
            e[i * 4 + 2] = expf(bf_lo(s.y) - mx); e[i * 4 + 3] = expf(bf_hi(s.y) - mx);
            sum += (e[i * 4] + e[i * 4 + 1]) + (e[i * 4 + 2] + e[i * 4 + 3]);
        }
        sum = warp_sum(sum);
        if (lane == 0) sm_m[8 + warp] = sum;
        cbar();
        sum = 0.f;
#pragma unroll
        for (int w = 0; w < 8; w++) sum += sm_m[8 + w];
        const float inv = 1.0f / sum;
#pragma unroll
        for (int i = 0; i < 4; i++)
            *reinterpret_cast<uint2*>(sc + i * 1024 + tid * 4) =
                make_uint2(pack_bf(e[i * 4] * inv, e[i * 4 + 1] * inv), pack_bf(e[i * 4 + 2] * inv, e[i * 4 + 3] * inv));
        cbar();
    }
    CK32(11);
    PROF(tid == 0, 4);
    if (tid == 0) st_rlx32(g_epoch[cta], epoch + 1);

    uint4 ov = make_uint4(0, 0, 0, 0);
    {
        float oa[4][4] = {}, ob[4][4] = {};
        const uint32_t va = pin(sb + OFF_RING + ((lane >> 3) & 1) * 4096 + (warp >> 1) * 1024 + (lane & 7) * 128 +
                                ((((warp & 1) * 4 + (lane >> 4)) ^ (lane & 7)) << 4));
        auto pv_tile = [&](int t) {
            const int st = t & (NS - 1);
            const uint4 p = lds128(sb + OFF_A + t * 64 + t4 * 16);
            const uint32_t va0 = pin(va + st * STAGE), va1 = pin(va0 ^ 32);
            mbar_wait(bar_full + st * 8, ((KT + t) / NS) & 1);
            const uint4 v0 = ldm4t(va0), v1 = ldm4t(va1), v2 = ldm4t(va0 + 8192), v3 = ldm4t(va1 + 8192);
            mma16816(oa[0], p.x, p.y, p.z, p.w, v0.x, v0.y);
            mma16816(oa[1], p.x, p.y, p.z, p.w, v0.z, v0.w);
            mma16816(oa[2], p.x, p.y, p.z, p.w, v1.x, v1.y);
            mma16816(oa[3], p.x, p.y, p.z, p.w, v1.z, v1.w);
            mma16816(ob[0], p.x, p.y, p.z, p.w, v2.x, v2.y);
            mma16816(ob[1], p.x, p.y, p.z, p.w, v2.z, v2.w);
            mma16816(ob[2], p.x, p.y, p.z, p.w, v3.x, v3.y);
            mma16816(ob[3], p.x, p.y, p.z, p.w, v3.z, v3.w);
            if (lane == 0) mbar_arrive(bar_empty + st * 8);
        };
#pragma unroll 1
        for (int t = 0; t < KT - OEARLY; t++) pv_tile(t);
        ld_rlx128_if(tail, ov, p_o_ld);
#pragma unroll 1
        for (int t = KT - OEARLY; t < KT; t++) pv_tile(t);
        CK32(0);
        st_rlx128_if(lane < 4, p_o_st,
                     enc(pack_bf(oa[0][0] + ob[0][2], oa[0][1] + ob[0][3])), enc(pack_bf(oa[1][0] + ob[1][2], oa[1][1] + ob[1][3])),
                     enc(pack_bf(oa[2][0] + ob[2][2], oa[2][1] + ob[2][3])), enc(pack_bf(oa[3][0] + ob[3][2], oa[3][1] + ob[3][3])));
        CK32(1);
    }

    if (!tail) {
        if (warp < 7) {
            const uint32_t iv = par ^ 1;
            uint4 v0 = make_uint4(iv, iv, iv, iv), v1 = v0, v2 = v0, v3 = v0;
            poll_tag4(v0, v1, v2, v3, p_in, par);
            CK32(4);
            float a0 = (__uint_as_float(v0.x) + __uint_as_float(v1.x)) + (__uint_as_float(v2.x) + __uint_as_float(v3.x));
            float a1 = (__uint_as_float(v0.y) + __uint_as_float(v1.y)) + (__uint_as_float(v2.y) + __uint_as_float(v3.y));
            float a2 = (__uint_as_float(v0.z) + __uint_as_float(v1.z)) + (__uint_as_float(v2.z) + __uint_as_float(v3.z));
            float a3 = (__uint_as_float(v0.w) + __uint_as_float(v1.w)) + (__uint_as_float(v2.w) + __uint_as_float(v3.w));
#pragma unroll
            for (int o = 8; o <= 16; o <<= 1) {
                a0 += __shfl_xor_sync(0xffffffffu, a0, o);
                a1 += __shfl_xor_sync(0xffffffffu, a1, o);
                a2 += __shfl_xor_sync(0xffffffffu, a2, o);
                a3 += __shfl_xor_sync(0xffffffffu, a3, o);
            }
            st_rlx64_if(lane < 8 * HREP, p_res, enc(add_bf2(c0w, pack_bf(a0, a2))), enc(add_bf2(c1w, pack_bf(a1, a3))));
            CK32(5);
        }
        CKOUT();
        return;
    }

    {
        uint4 v = ov;
        ld_rlx128_if(min(min(v.x, v.y), min(v.z, v.w)) == 0, v, p_o_ld);
        mbar_wait(bar_empty + (RED_TILE % NS) * 8, (RED_TILE / NS) & 1);
        mbar_wait(bar_w, 0);
        uint4 a[2][4];
#pragma unroll
        for (int s = 0; s < 2; s++)
#pragma unroll
            for (int mt = 0; mt < 4; mt++) a[s][mt] = ldm4t((a_wo ^ (mt << 5)) + s * 2048);
        poll_nz(v, p_o_ld);
        CK32(2);
        float acc[4][4] = {};
#pragma unroll
        for (int mt = 0; mt < 4; mt++) mma16816(acc[mt], a[0][mt].x, a[0][mt].y, a[0][mt].z, a[0][mt].w, v.x, v.y);
#pragma unroll
        for (int mt = 0; mt < 4; mt++) mma16816(acc[mt], a[1][mt].x, a[1][mt].y, a[1][mt].z, a[1][mt].w, v.z, v.w);
#pragma unroll
        for (int mt = 0; mt < 4; mt += 2) {
            sts128(a_r2w + mt * 512, acc[mt][0], acc[mt][2], acc[mt][1], acc[mt][3]);
            sts128(a_r2w + mt * 512 + 512, acc[mt + 1][1], acc[mt + 1][3], acc[mt + 1][0], acc[mt + 1][2]);
        }
        cbar();
        float2 p[8];
#pragma unroll
        for (int w = 0; w < 8; w++) p[w] = lds64f(a_r2r + w * 2048);
        const float s0 = ((p[0].x + p[1].x) + (p[2].x + p[3].x)) + ((p[4].x + p[5].x) + (p[6].x + p[7].x));
        const float s1 = ((p[0].y + p[1].y) + (p[2].y + p[3].y)) + ((p[4].y + p[5].y) + (p[6].y + p[7].y));
        st_rlx64(p_p2_st, (__float_as_uint(s0) & ~1u) | par, (__float_as_uint(s1) & ~1u) | par);
        if (lane == 0) asm volatile("mbarrier.arrive.relaxed.cta.shared.b64 _, [%0];" :: "r"(bar_w + 8) : "memory");
    }
    CK32(3);

    if (!ffn2) {
        if (warp < 7) {
            uint4 v0 = ld_rlx128(p_in), v1 = ld_rlx128(p_in + 128);
            const uint32_t a_part = pin(sb + OFF_B + warp * 1024 + lane * 16);
            mbar_wait(bar_w + 16, 0);
            uint4 bw[4][2];
#pragma unroll
            for (int s = 0; s < 4; s++) {
                bw[s][0] = ldm4t(a_w1 + warp * 4096 + s * 1024);
                bw[s][1] = ldm4t((a_w1 ^ 32) + warp * 4096 + s * 1024);
            }
            poll_nz2(v0, v1, p_in);
            CK32(6);
            const uint32_t hw[8] = {v0.x, v0.y, v0.z, v0.w, v1.x, v1.y, v1.z, v1.w};
            float c[4][4] = {}, cs[4] = {};
#pragma unroll
            for (int s = 0; s < 4; s++) {
                mma16816(cs, hw[2 * s], ONES, hw[2 * s + 1], ONES, hw[2 * s], hw[2 * s + 1]);
                mma16816(c[0], hw[2 * s], ONES, hw[2 * s + 1], ONES, bw[s][0].x, bw[s][0].y);
                mma16816(c[1], hw[2 * s], ONES, hw[2 * s + 1], ONES, bw[s][0].z, bw[s][0].w);
                mma16816(c[2], hw[2 * s], ONES, hw[2 * s + 1], ONES, bw[s][1].x, bw[s][1].y);
                mma16816(c[3], hw[2 * s], ONES, hw[2 * s + 1], ONES, bw[s][1].z, bw[s][1].w);
            }
            if (t4 == (g >> 1)) sts64(a_stat + warp * 64, (g & 1) ? cs[3] : cs[2], (g & 1) ? cs[1] : cs[0]);
            sts128(a_part, c[0][0], c[0][1], c[1][0], c[1][1]);
            sts128(a_part + 512, c[2][0], c[2][1], c[3][0], c[3][1]);
            asm volatile("bar.arrive 2, 288;" ::: "memory");
            CK32(7);
        } else {
            ffn1_finish(bar_w + 16, a_w1, pin(sb + OFF_B + lane * 16), a_stat, c0w, c1w, p_res);
            CK32(8);
        }
    } else if (warp < 7) {
        const uint32_t a0 = pin(sb + OFF_RING + warp * 8192 +
                                (((lane >> 2) & 1) * 18 + (lane >> 4) * 8 + ((lane >> 1) & 1) * 4 + (lane & 1)) * 32 +
                                ((((lane >> 3) ^ (lane >> 1)) & 1) << 4));
        const uint32_t a_r5 = pin(sb + OFF_C + warp * 256 + (t4 >> 1) * 1856 + (g * 2 + (t4 & 1)) * 16);
        mbar_wait(bar_w + (2 + warp) * 8, 0);
        uint4 aw[2][8];
#pragma unroll
        for (int hh = 0; hh < 2; hh++)
#pragma unroll
            for (int s = 0; s < 8; s++) aw[hh][s] = ldm4t((a0 ^ ((s & 1) << 6)) + hh * 4096 + (s >> 1) * 1024);
        asm volatile("bar.sync 6, 256;" ::: "memory");
        uint4 u[4];
#pragma unroll
        for (int i = 0; i < 4; i++) u[i] = ld_rlx128(p_in + i * 64);
        poll_sign4(u[0], u[1], u[2], u[3], p_in);
        CK32(9);
        float y[2][2][4] = {};
#pragma unroll
        for (int i = 0; i < 4; i++)
#pragma unroll
            for (int hh = 0; hh < 2; hh++) {
                mma16816(y[hh][0], aw[hh][2 * i].x, aw[hh][2 * i].y, aw[hh][2 * i].z, aw[hh][2 * i].w, u[i].x, u[i].y);
                mma16816(y[hh][1], aw[hh][2 * i + 1].x, aw[hh][2 * i + 1].y, aw[hh][2 * i + 1].z, aw[hh][2 * i + 1].w, u[i].z, u[i].w);
            }
        const bool lo = t4 < 2;
        sts128(a_r5, lo ? y[0][0][0] + y[0][1][0] : y[1][0][0] + y[1][1][0], lo ? y[0][0][1] + y[0][1][1] : y[1][0][1] + y[1][1][1],
               lo ? y[0][0][2] + y[0][1][2] : y[1][0][2] + y[1][1][2], lo ? y[0][0][3] + y[0][1][3] : y[1][0][3] + y[1][1][3]);
        asm volatile("bar.arrive 4, 256;" ::: "memory");
    } else {
        uint32_t h0, h1;
        poll_nz_pair(h0, h1, p_in);
        asm volatile("bar.arrive 6, 256;" ::: "memory");
        const uint32_t hres = __byte_perm(h0, h1, (g & 1) ? 0x7632 : 0x5410);
        const uint32_t a_r5 = pin(sb + OFF_C + lane * 8);
        asm volatile("bar.sync 4, 256;" ::: "memory");
        float2 y[14];
#pragma unroll
        for (int w = 0; w < 14; w++) y[w] = lds64f(a_r5 + w * 256 + (w >= 7 ? 64 : 0));
        const float y0 = (((y[0].x + y[1].x) + (y[2].x + y[3].x)) + ((y[4].x + y[5].x) + (y[6].x + y[7].x))) +
                         (((y[8].x + y[9].x) + (y[10].x + y[11].x)) + (y[12].x + y[13].x));
        const float y1 = (((y[0].y + y[1].y) + (y[2].y + y[3].y)) + ((y[4].y + y[5].y) + (y[6].y + y[7].y))) +
                         (((y[8].y + y[9].y) + (y[10].y + y[11].y)) + (y[12].y + y[13].y));
        const uint32_t res = add_bf2(hres, add_bf2(pack_bf(-y0, -y1), c0w));
        asm volatile("st.global.u16 [%0], %1;" :: "l"(p_res), "h"((uint16_t)res) : "memory");
        asm volatile("st.global.u16 [%0+%2], %1;" :: "l"(p_res), "h"((uint16_t)(res >> 16)), "n"(DM * 2) : "memory");
        CK32(10);
    }
    CKOUT();
}

typedef CUresult (*EncodeTiledFn)(CUtensorMap*, CUtensorMapDataType, cuuint32_t, void*, const cuuint64_t*,
                                  const cuuint64_t*, const cuuint32_t*, const cuuint32_t*, CUtensorMapInterleave,
                                  CUtensorMapSwizzle, CUtensorMapL2promotion, CUtensorMapFloatOOBfill);

void encode_2d(EncodeTiledFn fn, CUtensorMap* tm, void* base, int rows, int cols, int box_rows, int box_cols,
               CUtensorMapSwizzle sw) {
    cuuint64_t dims[2] = {(cuuint64_t)cols, (cuuint64_t)rows};
    cuuint64_t strides[1] = {(cuuint64_t)cols * 2};
    cuuint32_t box[2] = {(cuuint32_t)box_cols, (cuuint32_t)box_rows};
    cuuint32_t es[2] = {1, 1};
    fn(tm, CU_TENSOR_MAP_DATA_TYPE_BFLOAT16, 2, base, dims, strides, box, es, CU_TENSOR_MAP_INTERLEAVE_NONE, sw,
       CU_TENSOR_MAP_L2_PROMOTION_L2_128B, CU_TENSOR_MAP_FLOAT_OOB_FILL_NONE);
}

void encode_kv(EncodeTiledFn fn, CUtensorMap* tm, void* base) {
    cuuint64_t dims[4] = {64, 8, 4, (cuuint64_t)NB * NH * SK / 8};
    cuuint64_t strides[3] = {DH * 2, 128, 8 * DH * 2};
    cuuint32_t box[4] = {64, 8, 4, TILE_KEYS / 8};
    cuuint32_t es[4] = {1, 1, 1, 1};
    fn(tm, CU_TENSOR_MAP_DATA_TYPE_BFLOAT16, 4, base, dims, strides, box, es, CU_TENSOR_MAP_INTERLEAVE_NONE,
       CU_TENSOR_MAP_SWIZZLE_128B, CU_TENSOR_MAP_L2_PROMOTION_NONE, CU_TENSOR_MAP_FLOAT_OOB_FILL_NONE);
}

}

extern "C" void kernel_launch(void* const* d_in, const int* in_sizes, int n_in, void* d_out, int out_size) {
    (void)in_sizes; (void)n_in; (void)out_size;
    static EncodeTiledFn encode = nullptr;
    if (!encode) {
        void* fn = nullptr;
        cudaDriverEntryPointQueryResult qr;
        cudaGetDriverEntryPoint("cuTensorMapEncodeTiled", &fn, cudaEnableDefault, &qr);
        encode = (EncodeTiledFn)fn;
        cudaFuncSetAttribute(fused_decode_kernel, cudaFuncAttributeMaxDynamicSharedMemorySize, SMEM_BYTES);
    }
    CUtensorMap tm_k, tm_v, tm_wo, tm_w1, tm_w2;
    encode_kv(encode, &tm_k, d_in[1]);
    encode_kv(encode, &tm_v, d_in[2]);
    encode_2d(encode, &tm_wo, d_in[4], NH * DH, DM, 256, 64, CU_TENSOR_MAP_SWIZZLE_128B);
    encode_2d(encode, &tm_w1, d_in[6], DM, FF, 224, 32, CU_TENSOR_MAP_SWIZZLE_64B);
    encode_2d(encode, &tm_w2, d_in[8], FF, DM, 256, 16, CU_TENSOR_MAP_SWIZZLE_32B);
    fused_decode_kernel<<<NCTA, NTHREADS, SMEM_BYTES, cudaStreamPerThread>>>(
        (const __nv_bfloat16*)d_in[0], (const __nv_bfloat16*)d_in[3], (const __nv_bfloat16*)d_in[7],
        (const __nv_bfloat16*)d_in[9], (__nv_bfloat16*)d_out, tm_k, tm_v, tm_wo, tm_w1, tm_w2);
}
```

```cpp
#include <cuda_runtime.h>
#include <cuda_bf16.h>
#include <cuda.h>
#include <stdint.h>

namespace {

constexpr int NB = 8, DM = 448, NH = 16, SK = 4096, DH = 256, FF = 1792;
constexpr int NCTA = NB * NH;
constexpr int NMSG = FF / 16;
constexpr int TILE_KEYS = 32;
constexpr int STAGE = TILE_KEYS * DH * 2;
constexpr int NS = 8;
constexpr int KT = SK / TILE_KEYS;
constexpr int NT = 2 * KT;
constexpr int NTHREADS = 320;
constexpr int XP = 456;
constexpr int SPIN_MAX = 1 << 22;

#define WIN 416
#define EXTRA 192
#define XO 1
#define HREP 2
#define OEARLY 3
constexpr int D0 = 3;
constexpr int HSLEEP = 300;

constexpr int OFF_RING = 0;
constexpr int OFF_WO = OFF_RING + NS * STAGE;
constexpr int OFF_W = OFF_WO + DH * 128;
constexpr int OFF_A = OFF_W + DM * 64;
constexpr int OFF_B = OFF_A + SK * 2;
constexpr int OFF_Q = OFF_B + 8960;
constexpr int OFF_C = OFF_Q + 512;
constexpr int OFF_M = OFF_C + NB * XP * 2;
constexpr int OFF_BAR = OFF_M + 128;
constexpr int SMEM_BYTES = OFF_BAR + (2 * NS + 9) * 8;
static_assert(SMEM_BYTES <= 232448, "shared memory budget");

__device__ __align__(128) uint32_t g_epoch[NCTA][32];
__device__ __align__(128) uint32_t g_prog[2][32];
__device__ __align__(128) uint32_t g_q[2][NB * NH * DH / 2];
__device__ __align__(128) uint32_t g_o[2][NH * NB * DH / 2];
__device__ __align__(128) uint32_t g_h[2][HREP][NB * DM / 2];
__device__ __align__(128) uint32_t g_g[2][2 * NMSG * 32];
__device__ __align__(128) uint32_t g_p2[7 * 16 * 16 * 32];

#define PROF(cond, i)
#define CKDECL
#define CK32(i)
#define CKOUT()

__device__ __forceinline__ uint32_t smem_u32(const void* p) { return (uint32_t)__cvta_generic_to_shared(p); }

__device__ __forceinline__ void mbar_init(uint32_t a, uint32_t c) {
    asm volatile("mbarrier.init.shared.b64 [%0], %1;" :: "r"(a), "r"(c) : "memory");
}
__device__ __forceinline__ void mbar_expect_tx(uint32_t a, uint32_t bytes) {
    asm volatile("mbarrier.arrive.expect_tx.shared.b64 _, [%0], %1;" :: "r"(a), "r"(bytes) : "memory");
}
__device__ __forceinline__ void mbar_arrive(uint32_t a) {
    asm volatile("mbarrier.arrive.shared.b64 _, [%0];" :: "r"(a) : "memory");
}
__device__ __forceinline__ void mbar_arrive2(uint32_t a) {
    asm volatile("mbarrier.arrive.shared.b64 _, [%0], 2;" :: "r"(a) : "memory");
}
__device__ __forceinline__ bool mbar_test(uint32_t a, uint32_t parity) {
    uint32_t ok;
    asm volatile("{\n.reg .pred p;\nmbarrier.test_wait.parity.shared.b64 p, [%1], %2;\nselp.u32 %0, 1, 0, p;\n}"
                 : "=r"(ok) : "r"(a), "r"(parity) : "memory");
    return ok;
}
__device__ __forceinline__ uint32_t clock32() {
    uint32_t c;
    asm volatile("mov.u32 %0, %%clock;" : "=r"(c));
    return c;
}
__device__ __forceinline__ void mbar_wait(uint32_t a, uint32_t parity) {
    uint32_t ok;
    int it = 0;
    do {
        asm volatile("{\n.reg .pred p;\nmbarrier.try_wait.parity.shared.b64 p, [%1], %2;\nselp.u32 %0, 1, 0, p;\n}"
                     : "=r"(ok) : "r"(a), "r"(parity) : "memory");
    } while (!ok && ++it < SPIN_MAX);
}
__device__ __forceinline__ void tma_tile(uint32_t dst, const CUtensorMap* tm, int group, uint32_t bar, uint64_t pol) {
    asm volatile("cp.async.bulk.tensor.4d.shared::cluster.global.mbarrier::complete_tx::bytes.L2::cache_hint"
                 " [%0], [%1, {%3, %3, %3, %4}], [%2], %5;"
                 :: "r"(dst), "l"(tm), "r"(bar), "r"(0), "r"(group), "l"(pol) : "memory");
}
__device__ __forceinline__ void tma_2d(uint32_t dst, const CUtensorMap* tm, int c0, int c1, uint32_t bar) {
    asm volatile("cp.async.bulk.tensor.2d.shared::cluster.global.mbarrier::complete_tx::bytes [%0], [%1, {%3, %4}], [%2];"
                 :: "r"(dst), "l"(tm), "r"(bar), "r"(c0), "r"(c1) : "memory");
}
__device__ __forceinline__ void cbar() { asm volatile("bar.sync 1, 256;" ::: "memory"); }

__device__ __forceinline__ uint4 lds128(uint32_t a) {
    uint4 v;
    asm volatile("ld.shared.v4.u32 {%0,%1,%2,%3}, [%4];" : "=r"(v.x), "=r"(v.y), "=r"(v.z), "=r"(v.w) : "r"(a) : "memory");
    return v;
}
__device__ __forceinline__ uint4 ldm4(uint32_t a) {
    uint4 v;
    asm volatile("ldmatrix.sync.aligned.m8n8.x4.shared.b16 {%0,%1,%2,%3}, [%4];"
                 : "=r"(v.x), "=r"(v.y), "=r"(v.z), "=r"(v.w) : "r"(a) : "memory");
    return v;
}
__device__ __forceinline__ uint4 ldm4t(uint32_t a) {
    uint4 v;
    asm volatile("ldmatrix.sync.aligned.m8n8.x4.trans.shared.b16 {%0,%1,%2,%3}, [%4];"
                 : "=r"(v.x), "=r"(v.y), "=r"(v.z), "=r"(v.w) : "r"(a) : "memory");
    return v;
}
__device__ __forceinline__ void mma16816(float (&c)[4], uint32_t a0, uint32_t a1, uint32_t a2, uint32_t a3, uint32_t b0, uint32_t b1) {
    asm volatile("mma.sync.aligned.m16n8k16.row.col.f32.bf16.bf16.f32 {%0,%1,%2,%3}, {%4,%5,%6,%7}, {%8,%9}, {%0,%1,%2,%3};"
                 : "+f"(c[0]), "+f"(c[1]), "+f"(c[2]), "+f"(c[3])
                 : "r"(a0), "r"(a1), "r"(a2), "r"(a3), "r"(b0), "r"(b1));
}
__device__ __forceinline__ uint4 ld_rlx128(const uint32_t* p) {
    uint4 v;
    asm volatile("ld.relaxed.gpu.global.v4.u32 {%0,%1,%2,%3}, [%4];" : "=r"(v.x), "=r"(v.y), "=r"(v.z), "=r"(v.w) : "l"(p) : "memory");
    return v;
}
__device__ __forceinline__ void ld_rlx128_if(bool c, uint4& v, const uint32_t* p) {
    asm volatile("{\n.reg .pred p;\nsetp.ne.u32 p, %5, 0;\n@p ld.relaxed.gpu.global.v4.u32 {%0,%1,%2,%3}, [%4];\n}"
                 : "+r"(v.x), "+r"(v.y), "+r"(v.z), "+r"(v.w) : "l"(p), "r"((uint32_t)c) : "memory");
}
__device__ __forceinline__ uint32_t ldg32_now(const void* p) {
    uint32_t v;
    asm volatile("ld.global.nc.u32 %0, [%1];" : "=r"(v) : "l"(p) : "memory");
    return v;
}
__device__ __forceinline__ uint4 ldg128_now(const void* p) {
    uint4 v;
    asm volatile("ld.global.nc.v4.u32 {%0,%1,%2,%3}, [%4];" : "=r"(v.x), "=r"(v.y), "=r"(v.z), "=r"(v.w) : "l"(p) : "memory");
    return v;
}
__device__ __forceinline__ void st_rlx32(uint32_t* p, uint32_t v) {
    asm volatile("st.relaxed.gpu.global.u32 [%0], %1;" :: "l"(p), "r"(v) : "memory");
}
__device__ __forceinline__ void st_rlx64(uint32_t* p, uint32_t a, uint32_t b) {
    asm volatile("st.relaxed.gpu.global.v2.u32 [%0], {%1,%2};" :: "l"(p), "r"(a), "r"(b) : "memory");
}

__device__ __forceinline__ void st_rlx64_if(bool c, uint32_t* p, uint32_t a, uint32_t b) {
    asm volatile("{\n.reg .pred p;\nsetp.ne.u32 p, %3, 0;\n@p st.relaxed.gpu.global.v2.u32 [%0], {%1,%2};\n}"
                 :: "l"(p), "r"(a), "r"(b), "r"((uint32_t)c) : "memory");
}

__device__ __forceinline__ void st_rlx128_if(bool c, uint32_t* p, uint32_t a, uint32_t b, uint32_t d, uint32_t e) {
    asm volatile("{\n.reg .pred p;\nsetp.ne.u32 p, %5, 0;\n@p st.relaxed.gpu.global.v4.u32 [%0], {%1,%2,%3,%4};\n}"
                 :: "l"(p), "r"(a), "r"(b), "r"(d), "r"(e), "r"((uint32_t)c) : "memory");
}
__device__ __forceinline__ float bf_lo(uint32_t w) { return __uint_as_float(w << 16); }
__device__ __forceinline__ float bf_hi(uint32_t w) { return __uint_as_float(w & 0xffff0000u); }
__device__ __forceinline__ uint32_t pack_bf(float lo, float hi) {
    __nv_bfloat162 v = __floats2bfloat162_rn(lo, hi);
    return *reinterpret_cast<uint32_t*>(&v);
}
__device__ __forceinline__ float rbf(float x) { return __uint_as_float(pack_bf(0.f, x)); }
__device__ __forceinline__ uint32_t enc(uint32_t w) { return w ? w : 0x80008000u; }

__device__ __forceinline__ float warp_sum(float v) {
#pragma unroll
    for (int o = 16; o > 0; o >>= 1) v += __shfl_xor_sync(0xffffffffu, v, o);
    return v;
}

__device__ __forceinline__ void layernorm_row(const uint4& r0, const uint4& r1, int lane, uint32_t dst_row) {
    const bool act = lane < 28;
    float v[16];
    const uint32_t w[8] = {r0.x, r0.y, r0.z, r0.w, r1.x, r1.y, r1.z, r1.w};
#pragma unroll
    for (int i = 0; i < 8; i++) { v[2 * i] = act ? bf_lo(w[i]) : 0.f; v[2 * i + 1] = act ? bf_hi(w[i]) : 0.f; }
    float s = 0.f;
#pragma unroll
    for (int i = 0; i < 16; i++) s += v[i];
    const float mean = warp_sum(s) / DM;
    float q = 0.f;
#pragma unroll
    for (int i = 0; i < 16; i++) { const float d = v[i] - mean; q = fmaf(d, d, q); }
    const float var = warp_sum(act ? q : 0.f) / DM;
    const float mb = rbf(mean);
    const float sd = rbf(sqrtf(rbf(rbf(var) + 1e-5f)));
    const float rs = 1.0f / sd;
    uint32_t o[8];
#pragma unroll
    for (int i = 0; i < 8; i++) o[i] = pack_bf(rbf(v[2 * i] - mb) * rs, rbf(v[2 * i + 1] - mb) * rs);
    if (act) {
        asm volatile("st.shared.v4.u32 [%0], {%1,%2,%3,%4};" :: "r"(dst_row + lane * 16), "r"(o[0]), "r"(o[1]), "r"(o[2]), "r"(o[3]) : "memory");
        asm volatile("st.shared.v4.u32 [%0], {%1,%2,%3,%4};" :: "r"(dst_row + 448 + lane * 16), "r"(o[4]), "r"(o[5]), "r"(o[6]), "r"(o[7]) : "memory");
    }
}

template <class T> __device__ __forceinline__ T* pin(T* p) { asm volatile("" : "+l"(p)); return p; }
__device__ __forceinline__ uint32_t pin(uint32_t v) { asm volatile("" : "+r"(v)); return v; }
__device__ __forceinline__ void sts64(uint32_t a, float x, float y) {
    asm volatile("st.shared.v2.f32 [%0], {%1,%2};" :: "r"(a), "f"(x), "f"(y) : "memory");
}
__device__ __forceinline__ void sts128(uint32_t a, float x, float y, float z, float w) {
    asm volatile("st.shared.v4.f32 [%0], {%1,%2,%3,%4};" :: "r"(a), "f"(x), "f"(y), "f"(z), "f"(w) : "memory");
}
__device__ __forceinline__ float2 lds64f(uint32_t a) {
    float2 v;
    asm volatile("ld.shared.v2.f32 {%0,%1}, [%2];" : "=f"(v.x), "=f"(v.y) : "r"(a) : "memory");
    return v;
}
__device__ __forceinline__ float4 lds128f(uint32_t a) {
    float4 v;
    asm volatile("ld.shared.v4.f32 {%0,%1,%2,%3}, [%4];" : "=f"(v.x), "=f"(v.y), "=f"(v.z), "=f"(v.w) : "r"(a) : "memory");
    return v;
}
__device__ __forceinline__ uint32_t add_bf2(uint32_t a, uint32_t b) {
    uint32_t d;
    asm("add.rn.bf16x2 %0, %1, %2;" : "=r"(d) : "r"(a), "r"(b));
    return d;
}
__device__ __forceinline__ uint32_t neg_sq_relu_bf2(uint32_t a) {
    uint32_t d;
    asm("{\n.reg .b32 r, n;\nmax.bf16x2 r, %1, %2;\nneg.bf16x2 n, r;\nmul.rn.bf16x2 %0, r, n;\n}" : "=r"(d) : "r"(a), "r"(0));
    return d;
}

#define V4(v) "+r"(v.x), "+r"(v.y), "+r"(v.z), "+r"(v.w)
#define POLL_HEAD(label) "mov.u32 it, 0;\n" label ":\nadd.u32 it, it, 1;\nsetp.lt.u32 c, it, 4194304;\n"
#define POLL_EXIT(label) "and.pred q, q, c;\nvote.sync.any.pred q, q, 0xffffffff;\n@!q bra " label "_END;\n"
#define POLL_LD(p, regs, addr) "@" p " ld.relaxed.gpu.global.v4.u32 {" regs "}, [" addr "];\n"
__device__ __forceinline__ void poll_nz(uint4& v, const uint32_t* p) {
    asm volatile("{\n.reg .pred p0, q, c;\n.reg .b32 t, it;\n" POLL_HEAD("PA")
                 "min.u32 t, %0, %1;\nmin.u32 t, t, %2;\nmin.u32 t, t, %3;\nsetp.eq.u32 p0, t, 0;\nmov.pred q, p0;\n"
                 POLL_EXIT("PA") POLL_LD("p0", "%0,%1,%2,%3", "%4") "bra PA;\nPA_END:\n}"
                 : V4(v) : "l"(p) : "memory");
}
__device__ __forceinline__ void poll_nz2(uint4& v, uint4& w, const uint32_t* p) {
    asm volatile("{\n.reg .pred p0, p1, q, c;\n.reg .b32 t, u, it;\n" POLL_HEAD("PB")
                 "min.u32 t, %0, %1;\nmin.u32 t, t, %2;\nmin.u32 t, t, %3;\nsetp.eq.u32 p0, t, 0;\n"
                 "min.u32 u, %4, %5;\nmin.u32 u, u, %6;\nmin.u32 u, u, %7;\nsetp.eq.u32 p1, u, 0;\nor.pred q, p0, p1;\n"
                 POLL_EXIT("PB") POLL_LD("p0", "%0,%1,%2,%3", "%8") POLL_LD("p1", "%4,%5,%6,%7", "%8+512") "bra PB;\nPB_END:\n}"
                 : V4(v), V4(w) : "l"(p) : "memory");
}
__device__ __forceinline__ void poll_nz_pair(uint32_t& v, uint32_t& w, const uint32_t* p) {
    asm volatile("{\n.reg .pred q, c;\n.reg .b32 t, it;\n" POLL_HEAD("PC")
                 "ld.relaxed.gpu.global.u32 %0, [%2];\nld.relaxed.gpu.global.u32 %1, [%2+64];\n"
                 "min.u32 t, %0, %1;\nsetp.eq.u32 q, t, 0;\n"
                 POLL_EXIT("PC") "bra PC;\nPC_END:\n}"
                 : "=&r"(v), "=&r"(w) : "l"(p) : "memory");
}
__device__ __forceinline__ void poll_tag4(uint4& a, uint4& b, uint4& c, uint4& d, const uint32_t* p, uint32_t tag) {
    asm volatile("{\n.reg .pred p0, p1, p2, p3, q, c;\n.reg .b32 t, u, it;\n" POLL_HEAD("PD")
                 "lop3.b32 t, %0, %1, %17, 0x7e;\nlop3.b32 u, %2, %3, %17, 0x7e;\nlop3.b32 t, t, u, 1, 0xa8;\nsetp.ne.u32 p0, t, 0;\n"
                 "lop3.b32 t, %4, %5, %17, 0x7e;\nlop3.b32 u, %6, %7, %17, 0x7e;\nlop3.b32 t, t, u, 1, 0xa8;\nsetp.ne.u32 p1, t, 0;\n"
                 "lop3.b32 t, %8, %9, %17, 0x7e;\nlop3.b32 u, %10, %11, %17, 0x7e;\nlop3.b32 t, t, u, 1, 0xa8;\nsetp.ne.u32 p2, t, 0;\n"
                 "lop3.b32 t, %12, %13, %17, 0x7e;\nlop3.b32 u, %14, %15, %17, 0x7e;\nlop3.b32 t, t, u, 1, 0xa8;\nsetp.ne.u32 p3, t, 0;\n"
                 "or.pred q, p0, p1;\nor.pred q, q, p2;\nor.pred q, q, p3;\n"
                 POLL_EXIT("PD") POLL_LD("p0", "%0,%1,%2,%3", "%16") POLL_LD("p1", "%4,%5,%6,%7", "%16+512")
                 POLL_LD("p2", "%8,%9,%10,%11", "%16+1024") POLL_LD("p3", "%12,%13,%14,%15", "%16+1536") "bra PD;\nPD_END:\n}"
                 : V4(a), V4(b), V4(c), V4(d) : "l"(p), "r"(tag) : "memory");
}
__device__ __forceinline__ void poll_sign4(uint4& a, uint4& b, uint4& c, uint4& d, const uint32_t* p) {
    asm volatile("{\n.reg .pred p0, p1, p2, p3, q, c;\n.reg .b32 t, it;\n" POLL_HEAD("PE")
                 "lop3.b32 t, %0, %1, %2, 0x80;\nlop3.b32 t, t, %3, 0x80000000, 0x2a;\nsetp.ne.u32 p0, t, 0;\n"
                 "lop3.b32 t, %4, %5, %6, 0x80;\nlop3.b32 t, t, %7, 0x80000000, 0x2a;\nsetp.ne.u32 p1, t, 0;\n"
                 "lop3.b32 t, %8, %9, %10, 0x80;\nlop3.b32 t, t, %11, 0x80000000, 0x2a;\nsetp.ne.u32 p2, t, 0;\n"
                 "lop3.b32 t, %12, %13, %14, 0x80;\nlop3.b32 t, t, %15, 0x80000000, 0x2a;\nsetp.ne.u32 p3, t, 0;\n"
                 "or.pred q, p0, p1;\nor.pred q, q, p2;\nor.pred q, q, p3;\n"
                 POLL_EXIT("PE") POLL_LD("p0", "%0,%1,%2,%3", "%16") POLL_LD("p1", "%4,%5,%6,%7", "%16+256")
                 POLL_LD("p2", "%8,%9,%10,%11", "%16+512") POLL_LD("p3", "%12,%13,%14,%15", "%16+768") "bra PE;\nPE_END:\n}"
                 : V4(a), V4(b), V4(c), V4(d) : "l"(p) : "memory");
}

constexpr uint32_t ONES = 0x3f803f80u;

__device__ __forceinline__ void ffn1_finish(uint32_t bar, uint32_t a_w1, uint32_t a_part, uint32_t a_stat,
                                            uint32_t bias_a, uint32_t bias_b, uint32_t* dst) {
    float w0[4] = {}, w1[4] = {}, w2[4] = {}, w3[4] = {};
    mbar_wait(bar, 0);
#pragma unroll 1
    for (int s = 0; s < 28; s += 14) {
        uint4 bw[14];
#pragma unroll
        for (int i = 0; i < 14; i++) bw[i] = ldm4t(a_w1 + (s + i) * 1024);
#pragma unroll
        for (int i = 0; i < 14; i += 2) {
            mma16816(w0, ONES, ONES, ONES, ONES, bw[i].x, bw[i].y);
            mma16816(w1, ONES, ONES, ONES, ONES, bw[i].z, bw[i].w);
            mma16816(w2, ONES, ONES, ONES, ONES, bw[i + 1].x, bw[i + 1].y);
            mma16816(w3, ONES, ONES, ONES, ONES, bw[i + 1].z, bw[i + 1].w);
        }
    }
    const float cs0 = w0[0] + w2[0], cs1 = w0[1] + w2[1], cs2 = w1[0] + w3[0], cs3 = w1[1] + w3[1];
    asm volatile("bar.sync 2, 288;" ::: "memory");
    float2 sq[7];
    float4 p[7];
#pragma unroll
    for (int w = 0; w < 7; w++) sq[w] = lds64f(a_stat + w * 64);
#pragma unroll
    for (int w = 0; w < 7; w++) p[w] = lds128f(a_part + w * 1024);
    const float sum = ((sq[0].x + sq[1].x) + (sq[2].x + sq[3].x)) + ((sq[4].x + sq[5].x) + sq[6].x);
    const float mean = sum * (1.0f / DM);
    const float msq = (((sq[0].y + sq[1].y) + (sq[2].y + sq[3].y)) + ((sq[4].y + sq[5].y) + sq[6].y)) * (1.0f / DM);
    const float var = fmaxf(fmaf(-mean, mean, msq), 0.f);
    float sd, rs;
    asm("sqrt.approx.ftz.f32 %0, %1;" : "=f"(sd) : "f"(rbf(rbf(var) + 1e-5f)));
    asm("rcp.approx.ftz.f32 %0, %1;" : "=f"(rs) : "f"(rbf(sd)));
    const float mb = rbf(fmaf(fmaf(-mean, (float)DM, sum), 1.0f / DM, mean));
    const float s0 = fmaf(-mb, cs0, ((p[0].x + p[1].x) + (p[2].x + p[3].x)) + ((p[4].x + p[5].x) + p[6].x));
    const float s1 = fmaf(-mb, cs1, ((p[0].y + p[1].y) + (p[2].y + p[3].y)) + ((p[4].y + p[5].y) + p[6].y));
    const float s2 = fmaf(-mb, cs2, ((p[0].z + p[1].z) + (p[2].z + p[3].z)) + ((p[4].z + p[5].z) + p[6].z));
    const float s3 = fmaf(-mb, cs3, ((p[0].w + p[1].w) + (p[2].w + p[3].w)) + ((p[4].w + p[5].w) + p[6].w));
    st_rlx64(dst, neg_sq_relu_bf2(add_bf2(pack_bf(s0 * rs, s1 * rs), bias_a)),
             neg_sq_relu_bf2(add_bf2(pack_bf(s2 * rs, s3 * rs), bias_b)));
}

__global__ void __launch_bounds__(NTHREADS, 1)
fused_decode_kernel(const __nv_bfloat16* __restrict__ x, const __nv_bfloat16* __restrict__ wq,
                    const __nv_bfloat16* __restrict__ b1, const __nv_bfloat16* __restrict__ b2,
                    __nv_bfloat16* __restrict__ out,
                    const __grid_constant__ CUtensorMap tm_k, const __grid_constant__ CUtensorMap tm_v,
                    const __grid_constant__ CUtensorMap tm_wo, const __grid_constant__ CUtensorMap tm_w1,
                    const __grid_constant__ CUtensorMap tm_w2) {
    extern __shared__ __align__(1024) uint8_t sp[];
    const uint32_t sb = pin(smem_u32(sp));

    const int tid = threadIdx.x, warp = tid >> 5, lane = tid & 31;
    const int g = lane >> 2, t4 = lane & 3;
    const int cta = blockIdx.x;
    CKDECL;
    const int hd = cta >> 3, bj = cta & 7;
    const bool tail = bj < 7;
    const int ri = (hd * 7 + bj) >> 1;
    const bool ffn2 = (hd + bj) & 1;
    const int bg = ri & 1, cg = ri >> 1;
    const uint32_t bar_full = sb + OFF_BAR, bar_empty = bar_full + NS * 8, bar_w = bar_empty + NS * 8;
    const uint32_t s_wq = sb + OFF_WO, s_est = sb + OFF_M + 64;

    uint32_t epoch;
    asm volatile("ld.relaxed.gpu.global.u32 %0, [%1];" : "=r"(epoch) : "l"(g_epoch[cta]) : "memory");
    uint4 xr0 = make_uint4(0, 0, 0, 0), xr1 = xr0;
    if (warp < 8) {
        if (lane < 28) {
            xr0 = ldg128_now(x + warp * DM + lane * 8);
            xr1 = ldg128_now(x + warp * DM + 224 + lane * 8);
        }
        const int row = tid >> 2, ch = tid & 3;
        const uint32_t d = s_wq + row * 64 + ((ch ^ ((row >> 1) & 3)) << 4);
        const __nv_bfloat16* p = wq + (size_t)row * (NH * DH) + cta * 32 + ch * 8;
#pragma unroll
        for (int i = 0; i < 7; i++)
            asm volatile("cp.async.cg.shared.global.L2::128B [%0], [%1], 16;"
                         :: "r"(d + i * 4096), "l"(p + (size_t)i * 64 * (NH * DH)) : "memory");
    }
    const int grp0 = (bj * NH + hd) * (SK / 8), flip = (hd & 1) * (KT / 2);
    uint64_t pol;
    asm volatile("createpolicy.fractional.L2::evict_first.b64 %0, 1.0;" : "=l"(pol));
    PROF(tid == 288, 0);
    if (tid == 256) {
#pragma unroll
        for (int s = 0; s < D0; s++) mbar_init(bar_full + s * 8, 1);
        asm volatile("fence.mbarrier_init.release.cluster;" ::: "memory");
#pragma unroll
        for (int s = 0; s < D0; s++) {
            mbar_expect_tx(bar_full + s * 8, STAGE);
            tma_tile(sb + OFF_RING + s * STAGE, &tm_k, grp0 + (s ^ flip) * 4, bar_full + s * 8, pol);
        }
    }

    if (warp == 8) {
        if (lane == 0) {
#pragma unroll
            for (int s = D0; s < NS; s++) mbar_init(bar_full + s * 8, 1);
#pragma unroll
            for (int s = 0; s < NS; s++) mbar_init(bar_empty + s * 8, 8);
#pragma unroll
            for (int s = 0; s < 9; s++) mbar_init(bar_w + s * 8, s == 1 ? 8 : 1);
            asm volatile("fence.mbarrier_init.release.cluster;" ::: "memory");
            asm volatile("st.volatile.shared.v2.u32 [%0], {%1,%2};" :: "r"(s_est), "r"(0), "r"(clock32()) : "memory");
        }
        __syncwarp();
        asm volatile("bar.arrive 3, 288;" ::: "memory");
        asm volatile("bar.arrive 7, 64;" ::: "memory");
        if (lane != 0) return;
        asm volatile("prefetch.tensormap [%0];" :: "l"(&tm_v) : "memory");
        asm volatile("prefetch.tensormap [%0];" :: "l"(&tm_wo) : "memory");
        asm volatile("prefetch.tensormap [%0];" :: "l"(ffn2 ? &tm_w2 : &tm_w1) : "memory");
        uint32_t* prog = g_prog[(epoch + 1) & 1];
        uint32_t t = D0, landed = 0;
#pragma unroll 1
        for (int it = 0; t < NT && it < 16 * SPIN_MAX; it++) {
            if (landed < t && mbar_test(bar_full + (landed & (NS - 1)) * 8, (landed / NS) & 1)) {
                landed++;
                if (((landed + cta) & 3) == 0) asm volatile("red.relaxed.gpu.global.add.u32 [%0], 4;" :: "l"(prog) : "memory");
            }
            const uint32_t s = t & (NS - 1);
            if (t < NS) {
                if (t - landed >= D0) continue;
            } else {
                if (t - landed >= NS) continue;
                if (t - landed >= 2) {
                    uint32_t v, c0;
                    asm volatile("ld.volatile.shared.v2.u32 {%0,%1}, [%2];" : "=r"(v), "=r"(c0) : "r"(s_est) : "memory");
                    if (t * NCTA > v + min(((clock32() - c0) * 7) >> 6, 256u) + (t - landed > 2 ? WIN : WIN + EXTRA)) continue;
                }
                if (!mbar_test(bar_empty + s * 8, (t / NS - 1) & 1)) continue;
            }
            mbar_expect_tx(bar_full + s * 8, STAGE);
            tma_tile(sb + OFF_RING + s * STAGE, t < KT ? &tm_k : &tm_v, grp0 + ((t ^ flip) & (KT - 1)) * 4, bar_full + s * 8, pol);
            t++;
        }
        asm volatile("red.relaxed.gpu.global.add.u32 [%0], %1;" :: "l"(prog), "r"(NT - ((landed + (cta & 3)) & ~3u)) : "memory");
        if (!tail) return;
        mbar_wait(bar_full + ((NT - 1 - XO) & (NS - 1)) * 8, ((NT - 1 - XO) / NS) & 1);
        mbar_expect_tx(bar_w, DH * 128);
        tma_2d(sb + OFF_WO, &tm_wo, bj * 64, hd * DH, bar_w);
        if (!ffn2) {
            mbar_wait(bar_w, 0);
            mbar_expect_tx(bar_w + 16, DM * 64);
            tma_2d(sb + OFF_W, &tm_w1, ri * 32, 0, bar_w + 16);
            tma_2d(sb + OFF_W + 224 * 64, &tm_w1, ri * 32, 224, bar_w + 16);
        } else {
            mbar_wait(bar_w + 8, 0);
#pragma unroll
            for (int i = 0; i < 7; i++) {
                mbar_expect_tx(bar_w + (2 + i) * 8, 8192);
                tma_2d(sb + OFF_RING + i * 8192, &tm_w2, cg * 16, i * 256, bar_w + (2 + i) * 8);
            }
        }
        return;
    }

    const uint32_t par = (epoch + 1) & 1;
    const uint32_t a_w1 = pin(sb + OFF_W + (((lane >> 3) & 1) * 8 + (lane & 7)) * 64 + (((lane >> 4) ^ ((lane >> 1) & 3)) << 4));
    const uint32_t a_stat = pin(sb + OFF_B + 7168 + g * 8);

    if (warp == 9) {
        uint32_t bias_a = 0, bias_b = 0;
        if (tail && !ffn2) {
            bias_a = ldg32_now(b1 + ri * 32 + 16 + t4 * 2);
            bias_b = ldg32_now(b1 + ri * 32 + 24 + t4 * 2);
        }
        uint4 q = make_uint4(0, 0, 0, 0);
        poll_nz(q, &g_q[par][bj * (NH * DH / 2) + hd * (DH / 2) + lane * 4]);
        *reinterpret_cast<uint4*>(sp + OFF_Q + lane * 16) = q;
        asm volatile("bar.arrive 5, 288;" ::: "memory");
        asm volatile("bar.sync 7, 64;" ::: "memory");
        if (lane == 0) {
            uint32_t v = 0;
#pragma unroll 1
            for (int it = 0; v + WIN < (NT - 1) * NCTA && it < SPIN_MAX; it++) {
                asm volatile("ld.relaxed.gpu.global.u32 %0, [%1];" : "=r"(v) : "l"(g_prog[par]) : "memory");
                asm volatile("st.volatile.shared.v2.u32 [%0], {%1,%2};" :: "r"(s_est), "r"(v), "r"(clock32()) : "memory");
                __nanosleep(HSLEEP);
            }
        }
        __syncwarp();
        if (tail && !ffn2) {
            ffn1_finish(bar_w + 16, a_w1 ^ 32, pin(sb + OFF_B + 512 + lane * 16), a_stat, bias_a, bias_b,
                        pin(&g_g[par][((g >> 2) * NMSG + ri * 2 + 1) * 32 + (g & 3) * 8 + (t4 ^ 1) * 2]));
            CK32(8);
            CKOUT();
        }
        return;
    }

    asm volatile("cp.async.commit_group;" ::: "memory");
    uint32_t c0w = 0, c1w = 0;
    if (!tail) {
        if (warp < 7) {
            const __nv_bfloat16* p = x + (hd >> 1) * DM + warp * 64 + (hd & 1) * 32 + ((lane >> 2) & 1) * 16 + t4 * 2;
            c0w = ldg32_now(p);
            c1w = ldg32_now(p + 8);
        }
    } else if (warp == 7) {
        if (ffn2) {
            c0w = ldg32_now(b2 + cg * 16 + (lane & 1) * 8 + (g & 6));
            c0w = __byte_perm(c0w, 0, (g & 1) ? 0x3232 : 0x1010);
        } else {
            c0w = ldg32_now(b1 + ri * 32 + t4 * 2);
            c1w = ldg32_now(b1 + ri * 32 + 8 + t4 * 2);
        }
    }

    layernorm_row(xr0, xr1, lane, sb + OFF_C + warp * (XP * 2));
    asm volatile("cp.async.wait_group 0;" ::: "memory");
    asm volatile("bar.sync 3, 288;" ::: "memory");

    float* red_b = reinterpret_cast<float*>(sp + OFF_B);
    if (warp < 7) {
        float acc[4][4] = {};
#pragma unroll
        for (int p = 0; p < 2; p++) {
            const uint4 a = ldm4(sb + OFF_C + (lane & 7) * (XP * 2) + (warp * 64 + p * 32 + (lane >> 3) * 8) * 2);
#pragma unroll
            for (int s = 0; s < 2; s++) {
                const int row = warp * 64 + p * 32 + s * 16 + ((lane >> 3) & 1) * 8 + (lane & 7);
#pragma unroll
                for (int np = 0; np < 2; np++) {
                    const int ch = np * 2 + (lane >> 4);
                    const uint4 bw = ldm4t(s_wq + row * 64 + ((ch ^ ((row >> 1) & 3)) << 4));
                    mma16816(acc[np * 2], s ? a.z : a.x, 0, s ? a.w : a.y, 0, bw.x, bw.y);
                    mma16816(acc[np * 2 + 1], s ? a.z : a.x, 0, s ? a.w : a.y, 0, bw.z, bw.w);
                }
            }
        }
#pragma unroll
        for (int n = 0; n < 4; n++)
            *reinterpret_cast<float2*>(red_b + (warp * 8 + g) * 40 + n * 8 + t4 * 2) = make_float2(acc[n][0], acc[n][1]);
    }
    asm volatile("fence.proxy.async.shared::cta;" ::: "memory");
    cbar();
    if (tid < 128) {
        const int b = tid >> 4, wd = tid & 15;
        float s0 = 0.f, s1 = 0.f;
#pragma unroll
        for (int w = 0; w < 7; w++) {
            const float2 p = *reinterpret_cast<const float2*>(red_b + (w * 8 + b) * 40 + wd * 2);
            s0 += p.x; s1 += p.y;
        }
        st_rlx32(&g_q[par][b * (NH * DH / 2) + cta * 16 + (wd & 3) * 4 + ((wd >> 2) & 1) * 2 + (wd >> 3)], enc(pack_bf(s0, s1)));
    } else {
        const int i = tid - 128;
        g_q[par ^ 1][cta * 128 + i] = 0;
        g_o[par ^ 1][cta * 128 + i] = 0;
        if (i < 56) g_g[par ^ 1][cta * 56 + i] = 0;
        if (i < 14 * HREP) (&g_h[0][0][0])[((par ^ 1) * NCTA + cta) * (14 * HREP) + i] = 0;
        if (cta == 0 && i == 0) g_prog[par ^ 1][0] = 0;
    }
    PROF(tid == 0, 1);

    uint32_t* const p_o_st = pin(&g_o[par][(hd * 8 + warp) * 128 + bj * 16 + t4 * 4]);
    const uint32_t* const p_o_ld = pin(&g_o[par][(hd * 8 + warp) * 128 + lane * 4]);
    uint32_t* const p_p2_st = pin(g_p2 + ((bj * 16 + warp * 2 + (lane >> 4)) * 16 + hd) * 32 + (lane & 15) * 2);
    const uint32_t* p_in;
    uint32_t* p_res;
    if (!tail) {
        p_in = g_p2 + ((warp * 16 + hd) * 16 + (lane >> 3)) * 32 + (lane & 7) * 4;
        p_res = &g_h[par][(lane >> 3) % HREP][(warp * 2 + (hd & 1)) * 128 + (hd >> 1) * 16 + t4 * 4 + ((lane >> 2) & 1) * 2];
    } else if (!ffn2) {
        p_in = &g_h[par][ri % HREP][warp * 256 + lane * 4];
        p_res = &g_g[par][((g >> 2) * NMSG + ri * 2) * 32 + (g & 3) * 8 + t4 * 2];
    } else {
        const int b = bg * 4 + (lane & 2);
        p_in = warp < 7 ? &g_g[par][(bg * NMSG + warp * 16 + (g >> 2) * 8 + (t4 >> 1)) * 32 + (g & 3) * 8 + (t4 & 1) * 4]
                        : &g_h[par][ri % HREP][(cg >> 1) * 128 + b * 16 + (g >> 1) * 4 + (cg & 1) * 2 + (lane & 1)];
        p_res = reinterpret_cast<uint32_t*>(out + b * DM + cg * 16 + (lane & 1) * 8 + g);
    }
    p_in = pin(p_in);
    p_res = pin(p_res);
    constexpr int RED_TILE = NT - 3;
    const uint32_t a_wo = pin(sb + OFF_WO + (warp * 32 + (lane >> 4) * 8 + (lane & 7)) * 128 + ((((lane >> 3) & 1) ^ (lane & 7)) << 4));
    const uint32_t a_r2w = pin(sb + OFF_RING + (RED_TILE % NS) * STAGE + warp * 2048 + (t4 * 8 + ((g + 2 * t4) & 7)) * 16);
    const uint32_t a_r2r = pin(sb + OFF_RING + (RED_TILE % NS) * STAGE + (lane >> 3) * 512 +
                               ((warp >> 1) * 8 + ((lane + (warp & 6)) & 7)) * 16 + ((warp ^ (lane >> 3)) & 1) * 8);
    __nv_bfloat16* sc = reinterpret_cast<__nv_bfloat16*>(sp + OFF_A);

    float mx = -INFINITY;
    {
        uint4 q[8];
        asm volatile("bar.sync 5, 288;" ::: "memory");
#pragma unroll
        for (int i = 0; i < 8; i++) q[i] = lds128(sb + OFF_Q + i * 64 + t4 * 16);
        PROF(tid == 0, 2);
        const uint32_t ka = pin(sb + OFF_RING + (warp & 3) * 4096 + (lane & 7) * 128 + (((lane >> 3) ^ (lane & 7)) << 4));
        uint32_t* scw = reinterpret_cast<uint32_t*>(sc) + t4 * 4 + (warp & 1) * 2 + ((warp >> 1) & 1);
#pragma unroll 1
        for (int t = warp >> 2; t < KT; t += 2) {
            const int st = t & (NS - 1);
            mbar_wait(bar_full + st * 8, (t / NS) & 1);
            uint4 kf[8];
#pragma unroll
            for (int i = 0; i < 8; i++) kf[i] = ldm4((ka ^ ((i & 1) << 6)) + st * STAGE + (i >> 1) * 1024);
            float c[4][4] = {};
#pragma unroll
            for (int i = 0; i < 8; i++) {
                mma16816(c[(i & 1) * 2], q[i].x, q[i].y, q[i].z, q[i].w, kf[i].x, kf[i].y);
                mma16816(c[(i & 1) * 2 + 1], q[i].x, q[i].y, q[i].z, q[i].w, kf[i].z, kf[i].w);
            }
            if (lane == 0) mbar_arrive2(bar_empty + st * 8);
            const uint32_t d = pack_bf((c[0][0] + c[2][0]) + (c[1][2] + c[3][2]), (c[0][1] + c[2][1]) + (c[1][3] + c[3][3]));
            const uint32_t sw = pack_bf(bf_lo(d) * 0.0625f, bf_hi(d) * 0.0625f);
            mx = fmaxf(mx, fmaxf(bf_lo(sw), bf_hi(sw)));
            if (lane < 4) scw[t * 16] = sw;
        }
    }
    PROF(tid == 0, 3);

    {
        float* sm_m = reinterpret_cast<float*>(sp + OFF_M);
        mx = fmaxf(mx, __shfl_xor_sync(0xffffffffu, mx, 1));
        mx = fmaxf(mx, __shfl_xor_sync(0xffffffffu, mx, 2));
        if (lane == 0) sm_m[warp] = mx;
        cbar();
#pragma unroll
        for (int w = 0; w < 8; w++) mx = fmaxf(mx, sm_m[w]);
        float e[16], sum = 0.f;
#pragma unroll
        for (int i = 0; i < 4; i++) {
            const uint2 s = *reinterpret_cast<const uint2*>(sc + i * 1024 + tid * 4);
            e[i * 4 + 0] = expf(bf_lo(s.x) - mx); e[i * 4 + 1] = expf(bf_hi(s.x) - mx);
            e[i * 4 + 2] = expf(bf_lo(s.y) - mx); e[i * 4 + 3] = expf(bf_hi(s.y) - mx);
            sum += (e[i * 4] + e[i * 4 + 1]) + (e[i * 4 + 2] + e[i * 4 + 3]);
        }
        sum = warp_sum(sum);
        if (lane == 0) sm_m[8 + warp] = sum;
        cbar();
        sum = 0.f;
#pragma unroll
        for (int w = 0; w < 8; w++) sum += sm_m[8 + w];
        const float inv = 1.0f / sum;
#pragma unroll
        for (int i = 0; i < 4; i++)
            *reinterpret_cast<uint2*>(sc + i * 1024 + tid * 4) =
                make_uint2(pack_bf(e[i * 4] * inv, e[i * 4 + 1] * inv), pack_bf(e[i * 4 + 2] * inv, e[i * 4 + 3] * inv));
        cbar();
    }
    CK32(11);
    PROF(tid == 0, 4);
    if (tid == 0) st_rlx32(g_epoch[cta], epoch + 1);

    uint4 ov = make_uint4(0, 0, 0, 0);
    {
        float oa[4][4] = {}, ob[4][4] = {};
        const uint32_t va = pin(sb + OFF_RING + ((lane >> 3) & 1) * 4096 + (warp >> 1) * 1024 + (lane & 7) * 128 +
                                ((((warp & 1) * 4 + (lane >> 4)) ^ (lane & 7)) << 4));
        auto pv_tile = [&](int t) {
            const int st = t & (NS - 1);
            const uint4 p = lds128(sb + OFF_A + t * 64 + t4 * 16);
            const uint32_t va0 = pin(va + st * STAGE), va1 = pin(va0 ^ 32);
            mbar_wait(bar_full + st * 8, ((KT + t) / NS) & 1);
            const uint4 v0 = ldm4t(va0), v1 = ldm4t(va1), v2 = ldm4t(va0 + 8192), v3 = ldm4t(va1 + 8192);
            mma16816(oa[0], p.x, p.y, p.z, p.w, v0.x, v0.y);
            mma16816(oa[1], p.x, p.y, p.z, p.w, v0.z, v0.w);
            mma16816(oa[2], p.x, p.y, p.z, p.w, v1.x, v1.y);
            mma16816(oa[3], p.x, p.y, p.z, p.w, v1.z, v1.w);
            mma16816(ob[0], p.x, p.y, p.z, p.w, v2.x, v2.y);
            mma16816(ob[1], p.x, p.y, p.z, p.w, v2.z, v2.w);
            mma16816(ob[2], p.x, p.y, p.z, p.w, v3.x, v3.y);
            mma16816(ob[3], p.x, p.y, p.z, p.w, v3.z, v3.w);
            if (lane == 0) mbar_arrive(bar_empty + st * 8);
        };
#pragma unroll 1
        for (int t = 0; t < KT - OEARLY; t++) pv_tile(t);
        ld_rlx128_if(tail, ov, p_o_ld);
#pragma unroll 1
        for (int t = KT - OEARLY; t < KT; t++) pv_tile(t);
        CK32(0);
        st_rlx128_if(lane < 4, p_o_st,
                     enc(pack_bf(oa[0][0] + ob[0][2], oa[0][1] + ob[0][3])), enc(pack_bf(oa[1][0] + ob[1][2], oa[1][1] + ob[1][3])),
                     enc(pack_bf(oa[2][0] + ob[2][2], oa[2][1] + ob[2][3])), enc(pack_bf(oa[3][0] + ob[3][2], oa[3][1] + ob[3][3])));
        CK32(1);
    }

    if (!tail) {
        if (warp < 7) {
            const uint32_t iv = par ^ 1;
            uint4 v0 = make_uint4(iv, iv, iv, iv), v1 = v0, v2 = v0, v3 = v0;
            poll_tag4(v0, v1, v2, v3, p_in, par);
            CK32(4);
            float a0 = (__uint_as_float(v0.x) + __uint_as_float(v1.x)) + (__uint_as_float(v2.x) + __uint_as_float(v3.x));
            float a1 = (__uint_as_float(v0.y) + __uint_as_float(v1.y)) + (__uint_as_float(v2.y) + __uint_as_float(v3.y));
            float a2 = (__uint_as_float(v0.z) + __uint_as_float(v1.z)) + (__uint_as_float(v2.z) + __uint_as_float(v3.z));
            float a3 = (__uint_as_float(v0.w) + __uint_as_float(v1.w)) + (__uint_as_float(v2.w) + __uint_as_float(v3.w));
#pragma unroll
            for (int o = 8; o <= 16; o <<= 1) {
                a0 += __shfl_xor_sync(0xffffffffu, a0, o);
                a1 += __shfl_xor_sync(0xffffffffu, a1, o);
                a2 += __shfl_xor_sync(0xffffffffu, a2, o);
                a3 += __shfl_xor_sync(0xffffffffu, a3, o);
            }
            st_rlx64_if(lane < 8 * HREP, p_res, enc(add_bf2(c0w, pack_bf(a0, a2))), enc(add_bf2(c1w, pack_bf(a1, a3))));
            CK32(5);
        }
        CKOUT();
        return;
    }

    {
        uint4 v = ov;
        ld_rlx128_if(min(min(v.x, v.y), min(v.z, v.w)) == 0, v, p_o_ld);
        mbar_wait(bar_empty + (RED_TILE % NS) * 8, (RED_TILE / NS) & 1);
        mbar_wait(bar_w, 0);
        uint4 a[2][4];
#pragma unroll
        for (int s = 0; s < 2; s++)
#pragma unroll
            for (int mt = 0; mt < 4; mt++) a[s][mt] = ldm4t((a_wo ^ (mt << 5)) + s * 2048);
        poll_nz(v, p_o_ld);
        CK32(2);
        float acc[4][4] = {};
#pragma unroll
        for (int mt = 0; mt < 4; mt++) mma16816(acc[mt], a[0][mt].x, a[0][mt].y, a[0][mt].z, a[0][mt].w, v.x, v.y);
#pragma unroll
        for (int mt = 0; mt < 4; mt++) mma16816(acc[mt], a[1][mt].x, a[1][mt].y, a[1][mt].z, a[1][mt].w, v.z, v.w);
#pragma unroll
        for (int mt = 0; mt < 4; mt += 2) {
            sts128(a_r2w + mt * 512, acc[mt][0], acc[mt][2], acc[mt][1], acc[mt][3]);
            sts128(a_r2w + mt * 512 + 512, acc[mt + 1][1], acc[mt + 1][3], acc[mt + 1][0], acc[mt + 1][2]);
        }
        cbar();
        float2 p[8];
#pragma unroll
        for (int w = 0; w < 8; w++) p[w] = lds64f(a_r2r + w * 2048);
        const float s0 = ((p[0].x + p[1].x) + (p[2].x + p[3].x)) + ((p[4].x + p[5].x) + (p[6].x + p[7].x));
        const float s1 = ((p[0].y + p[1].y) + (p[2].y + p[3].y)) + ((p[4].y + p[5].y) + (p[6].y + p[7].y));
        st_rlx64(p_p2_st, (__float_as_uint(s0) & ~1u) | par, (__float_as_uint(s1) & ~1u) | par);
        if (lane == 0) asm volatile("mbarrier.arrive.relaxed.cta.shared.b64 _, [%0];" :: "r"(bar_w + 8) : "memory");
    }
    CK32(3);

    if (!ffn2) {
        if (warp < 7) {
            uint4 v0 = ld_rlx128(p_in), v1 = ld_rlx128(p_in + 128);
            const uint32_t a_part = pin(sb + OFF_B + warp * 1024 + lane * 16);
            mbar_wait(bar_w + 16, 0);
            uint4 bw[4][2];
#pragma unroll
            for (int s = 0; s < 4; s++) {
                bw[s][0] = ldm4t(a_w1 + warp * 4096 + s * 1024);
                bw[s][1] = ldm4t((a_w1 ^ 32) + warp * 4096 + s * 1024);
            }
            poll_nz2(v0, v1, p_in);
            CK32(6);
            const uint32_t hw[8] = {v0.x, v0.y, v0.z, v0.w, v1.x, v1.y, v1.z, v1.w};
            float c[4][4] = {}, cs[4] = {};
#pragma unroll
            for (int s = 0; s < 4; s++) {
                mma16816(cs, hw[2 * s], ONES, hw[2 * s + 1], ONES, hw[2 * s], hw[2 * s + 1]);
                mma16816(c[0], hw[2 * s], ONES, hw[2 * s + 1], ONES, bw[s][0].x, bw[s][0].y);
                mma16816(c[1], hw[2 * s], ONES, hw[2 * s + 1], ONES, bw[s][0].z, bw[s][0].w);
                mma16816(c[2], hw[2 * s], ONES, hw[2 * s + 1], ONES, bw[s][1].x, bw[s][1].y);
                mma16816(c[3], hw[2 * s], ONES, hw[2 * s + 1], ONES, bw[s][1].z, bw[s][1].w);
            }
            if (t4 == (g >> 1)) sts64(a_stat + warp * 64, (g & 1) ? cs[3] : cs[2], (g & 1) ? cs[1] : cs[0]);
            sts128(a_part, c[0][0], c[0][1], c[1][0], c[1][1]);
            sts128(a_part + 512, c[2][0], c[2][1], c[3][0], c[3][1]);
            asm volatile("bar.arrive 2, 288;" ::: "memory");
            CK32(7);
        } else {
            ffn1_finish(bar_w + 16, a_w1, pin(sb + OFF_B + lane * 16), a_stat, c0w, c1w, p_res);
            CK32(8);
        }
    } else if (warp < 7) {
        const uint32_t a0 = pin(sb + OFF_RING + warp * 8192 +
                                (((lane >> 2) & 1) * 18 + (lane >> 4) * 8 + ((lane >> 1) & 1) * 4 + (lane & 1)) * 32 +
                                ((((lane >> 3) ^ (lane >> 1)) & 1) << 4));
        const uint32_t a_r5 = pin(sb + OFF_C + warp * 256 + (t4 >> 1) * 1856 + (g * 2 + (t4 & 1)) * 16);
        mbar_wait(bar_w + (2 + warp) * 8, 0);
        uint4 aw[2][8];
#pragma unroll
        for (int hh = 0; hh < 2; hh++)
#pragma unroll
            for (int s = 0; s < 8; s++) aw[hh][s] = ldm4t((a0 ^ ((s & 1) << 6)) + hh * 4096 + (s >> 1) * 1024);
        asm volatile("bar.sync 6, 256;" ::: "memory");
        uint4 u[4];
#pragma unroll
        for (int i = 0; i < 4; i++) u[i] = ld_rlx128(p_in + i * 64);
        poll_sign4(u[0], u[1], u[2], u[3], p_in);
        CK32(9);
        float y[2][2][4] = {};
#pragma unroll
        for (int i = 0; i < 4; i++)
#pragma unroll
            for (int hh = 0; hh < 2; hh++) {
                mma16816(y[hh][0], aw[hh][2 * i].x, aw[hh][2 * i].y, aw[hh][2 * i].z, aw[hh][2 * i].w, u[i].x, u[i].y);
                mma16816(y[hh][1], aw[hh][2 * i + 1].x, aw[hh][2 * i + 1].y, aw[hh][2 * i + 1].z, aw[hh][2 * i + 1].w, u[i].z, u[i].w);
            }
        const bool lo = t4 < 2;
        sts128(a_r5, lo ? y[0][0][0] + y[0][1][0] : y[1][0][0] + y[1][1][0], lo ? y[0][0][1] + y[0][1][1] : y[1][0][1] + y[1][1][1],
               lo ? y[0][0][2] + y[0][1][2] : y[1][0][2] + y[1][1][2], lo ? y[0][0][3] + y[0][1][3] : y[1][0][3] + y[1][1][3]);
        asm volatile("bar.arrive 4, 256;" ::: "memory");
    } else {
        uint32_t h0, h1;
        poll_nz_pair(h0, h1, p_in);
        asm volatile("bar.arrive 6, 256;" ::: "memory");
        const uint32_t hres = __byte_perm(h0, h1, (g & 1) ? 0x7632 : 0x5410);
        const uint32_t a_r5 = pin(sb + OFF_C + lane * 8);
        asm volatile("bar.sync 4, 256;" ::: "memory");
        float2 y[14];
#pragma unroll
        for (int w = 0; w < 14; w++) y[w] = lds64f(a_r5 + w * 256 + (w >= 7 ? 64 : 0));
        const float y0 = (((y[0].x + y[1].x) + (y[2].x + y[3].x)) + ((y[4].x + y[5].x) + (y[6].x + y[7].x))) +
                         (((y[8].x + y[9].x) + (y[10].x + y[11].x)) + (y[12].x + y[13].x));
        const float y1 = (((y[0].y + y[1].y) + (y[2].y + y[3].y)) + ((y[4].y + y[5].y) + (y[6].y + y[7].y))) +
                         (((y[8].y + y[9].y) + (y[10].y + y[11].y)) + (y[12].y + y[13].y));
        const uint32_t res = add_bf2(hres, add_bf2(pack_bf(-y0, -y1), c0w));
        asm volatile("st.global.u16 [%0], %1;" :: "l"(p_res), "h"((uint16_t)res) : "memory");
        asm volatile("st.global.u16 [%0+%2], %1;" :: "l"(p_res), "h"((uint16_t)(res >> 16)), "n"(DM * 2) : "memory");
        CK32(10);
    }
    CKOUT();
}

typedef CUresult (*EncodeTiledFn)(CUtensorMap*, CUtensorMapDataType, cuuint32_t, void*, const cuuint64_t*,
                                  const cuuint64_t*, const cuuint32_t*, const cuuint32_t*, CUtensorMapInterleave,
                                  CUtensorMapSwizzle, CUtensorMapL2promotion, CUtensorMapFloatOOBfill);

void encode_2d(EncodeTiledFn fn, CUtensorMap* tm, void* base, int rows, int cols, int box_rows, int box_cols,
               CUtensorMapSwizzle sw) {
    cuuint64_t dims[2] = {(cuuint64_t)cols, (cuuint64_t)rows};
    cuuint64_t strides[1] = {(cuuint64_t)cols * 2};
    cuuint32_t box[2] = {(cuuint32_t)box_cols, (cuuint32_t)box_rows};
    cuuint32_t es[2] = {1, 1};
    fn(tm, CU_TENSOR_MAP_DATA_TYPE_BFLOAT16, 2, base, dims, strides, box, es, CU_TENSOR_MAP_INTERLEAVE_NONE, sw,
       CU_TENSOR_MAP_L2_PROMOTION_L2_128B, CU_TENSOR_MAP_FLOAT_OOB_FILL_NONE);
}

void encode_kv(EncodeTiledFn fn, CUtensorMap* tm, void* base) {
    cuuint64_t dims[4] = {64, 8, 4, (cuuint64_t)NB * NH * SK / 8};
    cuuint64_t strides[3] = {DH * 2, 128, 8 * DH * 2};
    cuuint32_t box[4] = {64, 8, 4, TILE_KEYS / 8};
    cuuint32_t es[4] = {1, 1, 1, 1};
    fn(tm, CU_TENSOR_MAP_DATA_TYPE_BFLOAT16, 4, base, dims, strides, box, es, CU_TENSOR_MAP_INTERLEAVE_NONE,
       CU_TENSOR_MAP_SWIZZLE_128B, CU_TENSOR_MAP_L2_PROMOTION_NONE, CU_TENSOR_MAP_FLOAT_OOB_FILL_NONE);
}

}

extern "C" void kernel_launch(void* const* d_in, const int* in_sizes, int n_in, void* d_out, int out_size) {
    (void)in_sizes; (void)n_in; (void)out_size;
    static EncodeTiledFn encode = nullptr;
    if (!encode) {
        void* fn = nullptr;
        cudaDriverEntryPointQueryResult qr;
        cudaGetDriverEntryPoint("cuTensorMapEncodeTiled", &fn, cudaEnableDefault, &qr);
        encode = (EncodeTiledFn)fn;
        cudaFuncSetAttribute(fused_decode_kernel, cudaFuncAttributeMaxDynamicSharedMemorySize, SMEM_BYTES);
    }
    CUtensorMap tm_k, tm_v, tm_wo, tm_w1, tm_w2;
    encode_kv(encode, &tm_k, d_in[1]);
    encode_kv(encode, &tm_v, d_in[2]);
    encode_2d(encode, &tm_wo, d_in[4], NH * DH, DM, 256, 64, CU_TENSOR_MAP_SWIZZLE_128B);
    encode_2d(encode, &tm_w1, d_in[6], DM, FF, 224, 32, CU_TENSOR_MAP_SWIZZLE_64B);
    encode_2d(encode, &tm_w2, d_in[8], FF, DM, 256, 16, CU_TENSOR_MAP_SWIZZLE_32B);
    fused_decode_kernel<<<NCTA, NTHREADS, SMEM_BYTES, cudaStreamPerThread>>>(
        (const __nv_bfloat16*)d_in[0], (const __nv_bfloat16*)d_in[3], (const __nv_bfloat16*)d_in[7],
        (const __nv_bfloat16*)d_in[9], (__nv_bfloat16*)d_out, tm_k, tm_v, tm_wo, tm_w1, tm_w2);
}
```

```cpp
#include <cuda_runtime.h>
#include <cuda_bf16.h>
#include <cuda.h>
#include <stdint.h>

namespace {

constexpr int NB = 8, DM = 448, NH = 16, SK = 4096, DH = 256, FF = 1792;
constexpr int NCTA = NB * NH;
constexpr int NMSG = FF / 16;
constexpr int TILE_KEYS = 32;
constexpr int STAGE = TILE_KEYS * DH * 2;
constexpr int NS = 8;
constexpr int KT = SK / TILE_KEYS;
constexpr int NT = 2 * KT;
constexpr int NTHREADS = 352;
constexpr int XP = 456;
constexpr int SPIN_MAX = 1 << 22;

constexpr int D0 = 3;
constexpr int WIN = 416;
constexpr int EXTRA = 192;
constexpr int HSLEEP = 300;
constexpr int XO = 1;
constexpr int OEARLY = 3;
constexpr int HREP = 2;
constexpr int CLEAR_NS = 8000;

constexpr int OFF_RING = 0;
constexpr int OFF_WO = OFF_RING + NS * STAGE;
constexpr int OFF_W = OFF_WO + DH * 128;
constexpr int OFF_A = OFF_W + DM * 64;
constexpr int OFF_B = OFF_A + SK * 2;
constexpr int OFF_Q = OFF_B + 8960;
constexpr int OFF_C = OFF_Q + 512;
constexpr int OFF_D = OFF_C + NB * XP * 2;
constexpr int OFF_M = OFF_D + 7680;
constexpr int OFF_BAR = OFF_M + 128;
constexpr int SMEM_BYTES = OFF_BAR + (2 * NS + 9) * 8;
static_assert(SMEM_BYTES <= 232448, "shared memory budget");
static_assert(OFF_D - OFF_B >= 16384, "the wo reduction reuses the prologue areas");

__device__ __align__(128) uint32_t g_epoch[NCTA][32];
__device__ __align__(128) uint32_t g_prog[2][32];
__device__ __align__(128) uint32_t g_cleared[2][32];
__device__ __align__(128) uint32_t g_q[2][NB * NH * DH / 2];
struct __align__(128) Mail {
    uint32_t o[NH * NB * DH / 2];
    uint32_t p2[7 * 16 * 16 * 32];
    uint32_t h[HREP][NB * DM / 2];
    uint32_t g[2 * NMSG * 32];
};
__device__ Mail g_mail;
constexpr int MAIL_VECS = sizeof(Mail) / 16 / NCTA;
static_assert(sizeof(Mail) % (16 * NCTA) == 0, "equal shares");

__device__ __forceinline__ uint32_t smem_u32(const void* p) { return (uint32_t)__cvta_generic_to_shared(p); }

__device__ __forceinline__ void mbar_init(uint32_t a, uint32_t c) {
    asm volatile("mbarrier.init.shared.b64 [%0], %1;" :: "r"(a), "r"(c) : "memory");
}
__device__ __forceinline__ void mbar_expect_tx(uint32_t a, uint32_t bytes) {
    asm volatile("mbarrier.arrive.expect_tx.shared.b64 _, [%0], %1;" :: "r"(a), "r"(bytes) : "memory");
}
__device__ __forceinline__ void mbar_arrive(uint32_t a) {
    asm volatile("mbarrier.arrive.shared.b64 _, [%0];" :: "r"(a) : "memory");
}
__device__ __forceinline__ void mbar_arrive2(uint32_t a) {
    asm volatile("mbarrier.arrive.shared.b64 _, [%0], 2;" :: "r"(a) : "memory");
}
__device__ __forceinline__ bool mbar_test(uint32_t a, uint32_t parity) {
    uint32_t ok;
    asm volatile("{\n.reg .pred p;\nmbarrier.test_wait.parity.shared.b64 p, [%1], %2;\nselp.u32 %0, 1, 0, p;\n}"
                 : "=r"(ok) : "r"(a), "r"(parity) : "memory");
    return ok;
}
__device__ __forceinline__ uint32_t clock32() {
    uint32_t c;
    asm volatile("mov.u32 %0, %%clock;" : "=r"(c));
    return c;
}
__device__ __forceinline__ void mbar_wait(uint32_t a, uint32_t parity) {
    uint32_t ok;
    int it = 0;
    do {
        asm volatile("{\n.reg .pred p;\nmbarrier.try_wait.parity.shared.b64 p, [%1], %2;\nselp.u32 %0, 1, 0, p;\n}"
                     : "=r"(ok) : "r"(a), "r"(parity) : "memory");
    } while (!ok && ++it < SPIN_MAX);
    if (!ok) __trap();
}
__device__ __forceinline__ void tma_tile(uint32_t dst, const CUtensorMap* tm, int group, uint32_t bar, uint64_t pol) {
    asm volatile("cp.async.bulk.tensor.4d.shared::cluster.global.mbarrier::complete_tx::bytes.L2::cache_hint"
                 " [%0], [%1, {%3, %3, %3, %4}], [%2], %5;"
                 :: "r"(dst), "l"(tm), "r"(bar), "r"(0), "r"(group), "l"(pol) : "memory");
}
__device__ __forceinline__ void tma_2d(uint32_t dst, const CUtensorMap* tm, int c0, int c1, uint32_t bar) {
    asm volatile("cp.async.bulk.tensor.2d.shared::cluster.global.mbarrier::complete_tx::bytes [%0], [%1, {%3, %4}], [%2];"
                 :: "r"(dst), "l"(tm), "r"(bar), "r"(c0), "r"(c1) : "memory");
}
__device__ __forceinline__ void cbar() { asm volatile("barrier.sync 1, 256;" ::: "memory"); }

__device__ __forceinline__ uint4 lds128(uint32_t a) {
    uint4 v;
    asm volatile("ld.shared.v4.u32 {%0,%1,%2,%3}, [%4];" : "=r"(v.x), "=r"(v.y), "=r"(v.z), "=r"(v.w) : "r"(a) : "memory");
    return v;
}
__device__ __forceinline__ uint4 ldm4(uint32_t a) {
    uint4 v;
    asm volatile("ldmatrix.sync.aligned.m8n8.x4.shared.b16 {%0,%1,%2,%3}, [%4];"
                 : "=r"(v.x), "=r"(v.y), "=r"(v.z), "=r"(v.w) : "r"(a) : "memory");
    return v;
}
__device__ __forceinline__ uint4 ldm4t(uint32_t a) {
    uint4 v;
    asm volatile("ldmatrix.sync.aligned.m8n8.x4.trans.shared.b16 {%0,%1,%2,%3}, [%4];"
                 : "=r"(v.x), "=r"(v.y), "=r"(v.z), "=r"(v.w) : "r"(a) : "memory");
    return v;
}
__device__ __forceinline__ void mma16816(float (&c)[4], uint32_t a0, uint32_t a1, uint32_t a2, uint32_t a3, uint32_t b0, uint32_t b1) {
    asm volatile("mma.sync.aligned.m16n8k16.row.col.f32.bf16.bf16.f32 {%0,%1,%2,%3}, {%4,%5,%6,%7}, {%8,%9}, {%0,%1,%2,%3};"
                 : "+f"(c[0]), "+f"(c[1]), "+f"(c[2]), "+f"(c[3])
                 : "r"(a0), "r"(a1), "r"(a2), "r"(a3), "r"(b0), "r"(b1));
}
__device__ __forceinline__ uint4 ld_rlx128(const uint32_t* p) {
    uint4 v;
    asm volatile("ld.relaxed.gpu.global.v4.u32 {%0,%1,%2,%3}, [%4];" : "=r"(v.x), "=r"(v.y), "=r"(v.z), "=r"(v.w) : "l"(p) : "memory");
    return v;
}
__device__ __forceinline__ void ld_rlx128_if(bool c, uint4& v, const uint32_t* p) {
    asm volatile("{\n.reg .pred p;\nsetp.ne.u32 p, %5, 0;\n@p ld.relaxed.gpu.global.v4.u32 {%0,%1,%2,%3}, [%4];\n}"
                 : "+r"(v.x), "+r"(v.y), "+r"(v.z), "+r"(v.w) : "l"(p), "r"((uint32_t)c) : "memory");
}
__device__ __forceinline__ uint32_t ldg32_now(const void* p) {
    uint32_t v;
    asm volatile("ld.global.nc.u32 %0, [%1];" : "=r"(v) : "l"(p) : "memory");
    return v;
}
__device__ __forceinline__ uint4 ldg128_now(const void* p) {
    uint4 v;
    asm volatile("ld.global.nc.v4.u32 {%0,%1,%2,%3}, [%4];" : "=r"(v.x), "=r"(v.y), "=r"(v.z), "=r"(v.w) : "l"(p) : "memory");
    return v;
}
__device__ __forceinline__ void st_rlx32(uint32_t* p, uint32_t v) {
    asm volatile("st.relaxed.gpu.global.u32 [%0], %1;" :: "l"(p), "r"(v) : "memory");
}
__device__ __forceinline__ void st_rlx64(uint32_t* p, uint32_t a, uint32_t b) {
    asm volatile("st.relaxed.gpu.global.v2.u32 [%0], {%1,%2};" :: "l"(p), "r"(a), "r"(b) : "memory");
}

__device__ __forceinline__ void st_rlx64_if(bool c, uint32_t* p, uint32_t a, uint32_t b) {
    asm volatile("{\n.reg .pred p;\nsetp.ne.u32 p, %3, 0;\n@p st.relaxed.gpu.global.v2.u32 [%0], {%1,%2};\n}"
                 :: "l"(p), "r"(a), "r"(b), "r"((uint32_t)c) : "memory");
}

__device__ __forceinline__ void st_rlx128_if(bool c, uint32_t* p, uint32_t a, uint32_t b, uint32_t d, uint32_t e) {
    asm volatile("{\n.reg .pred p;\nsetp.ne.u32 p, %5, 0;\n@p st.relaxed.gpu.global.v4.u32 [%0], {%1,%2,%3,%4};\n}"
                 :: "l"(p), "r"(a), "r"(b), "r"(d), "r"(e), "r"((uint32_t)c) : "memory");
}
__device__ __forceinline__ float bf_lo(uint32_t w) { return __uint_as_float(w << 16); }
__device__ __forceinline__ float bf_hi(uint32_t w) { return __uint_as_float(w & 0xffff0000u); }
__device__ __forceinline__ uint32_t pack_bf(float lo, float hi) {
    __nv_bfloat162 v = __floats2bfloat162_rn(lo, hi);
    return *reinterpret_cast<uint32_t*>(&v);
}
__device__ __forceinline__ float rbf(float x) { return __uint_as_float(pack_bf(0.f, x)); }
__device__ __forceinline__ uint32_t enc(uint32_t w) { return w ? w : 0x80000000u; }

__device__ __forceinline__ float warp_sum(float v) {
#pragma unroll
    for (int o = 16; o > 0; o >>= 1) v += __shfl_xor_sync(0xffffffffu, v, o);
    return v;
}

__device__ __forceinline__ void layernorm_row(const uint4& r0, const uint4& r1, int lane, uint32_t dst_row) {
    const bool act = lane < 28;
    float v[16];
    const uint32_t w[8] = {r0.x, r0.y, r0.z, r0.w, r1.x, r1.y, r1.z, r1.w};
#pragma unroll
    for (int i = 0; i < 8; i++) { v[2 * i] = act ? bf_lo(w[i]) : 0.f; v[2 * i + 1] = act ? bf_hi(w[i]) : 0.f; }
    float s = 0.f;
#pragma unroll
    for (int i = 0; i < 16; i++) s += v[i];
    const float mean = warp_sum(s) / DM;
    float q = 0.f;
#pragma unroll
    for (int i = 0; i < 16; i++) { const float d = v[i] - mean; q = fmaf(d, d, q); }
    const float var = warp_sum(act ? q : 0.f) / DM;
    const float mb = rbf(mean);
    const float sd = rbf(sqrtf(rbf(rbf(var) + 1e-5f)));
    const float rs = 1.0f / sd;
    uint32_t o[8];
#pragma unroll
    for (int i = 0; i < 8; i++) o[i] = pack_bf(rbf(v[2 * i] - mb) * rs, rbf(v[2 * i + 1] - mb) * rs);
    if (act) {
        asm volatile("st.shared.v4.u32 [%0], {%1,%2,%3,%4};" :: "r"(dst_row + lane * 16), "r"(o[0]), "r"(o[1]), "r"(o[2]), "r"(o[3]) : "memory");
        asm volatile("st.shared.v4.u32 [%0], {%1,%2,%3,%4};" :: "r"(dst_row + 448 + lane * 16), "r"(o[4]), "r"(o[5]), "r"(o[6]), "r"(o[7]) : "memory");
    }
}

template <class T> __device__ __forceinline__ T* pin(T* p) { asm volatile("" : "+l"(p)); return p; }
__device__ __forceinline__ uint32_t pin(uint32_t v) { asm volatile("" : "+r"(v)); return v; }
__device__ __forceinline__ void sts64(uint32_t a, float x, float y) {
    asm volatile("st.shared.v2.f32 [%0], {%1,%2};" :: "r"(a), "f"(x), "f"(y) : "memory");
}
__device__ __forceinline__ void sts128(uint32_t a, float x, float y, float z, float w) {
    asm volatile("st.shared.v4.f32 [%0], {%1,%2,%3,%4};" :: "r"(a), "f"(x), "f"(y), "f"(z), "f"(w) : "memory");
}
__device__ __forceinline__ float2 lds64f(uint32_t a) {
    float2 v;
    asm volatile("ld.shared.v2.f32 {%0,%1}, [%2];" : "=f"(v.x), "=f"(v.y) : "r"(a) : "memory");
    return v;
}
__device__ __forceinline__ float4 lds128f(uint32_t a) {
    float4 v;
    asm volatile("ld.shared.v4.f32 {%0,%1,%2,%3}, [%4];" : "=f"(v.x), "=f"(v.y), "=f"(v.z), "=f"(v.w) : "r"(a) : "memory");
    return v;
}
__device__ __forceinline__ uint32_t add_bf2(uint32_t a, uint32_t b) {
    uint32_t d;
    asm("add.rn.bf16x2 %0, %1, %2;" : "=r"(d) : "r"(a), "r"(b));
    return d;
}
__device__ __forceinline__ uint32_t neg_sq_relu_bf2(uint32_t a) {
    uint32_t d;
    asm("{\n.reg .b32 r, n;\nmax.bf16x2 r, %1, %2;\nneg.bf16x2 n, r;\nmul.rn.bf16x2 %0, r, n;\n}" : "=r"(d) : "r"(a), "r"(0));
    return d;
}

#define V4(v) "+r"(v.x), "+r"(v.y), "+r"(v.z), "+r"(v.w)
#define POLL_HEAD(label) "mov.u32 it, 0;\n" label ":\nadd.u32 it, it, 1;\nsetp.lt.u32 c, it, 4194304;\n"
#define POLL_EXIT(label) "and.pred q, q, c;\nvote.sync.any.pred q, q, 0xffffffff;\n@!q bra " label "_END;\n"
#define POLL_LD(p, regs, addr) "@" p " ld.relaxed.gpu.global.v4.u32 {" regs "}, [" addr "];\n"
__device__ __forceinline__ void poll_nz(uint4& v, const uint32_t* p) {
    asm volatile("{\n.reg .pred p0, q, c;\n.reg .b32 t, it;\n" POLL_HEAD("PA")
                 "min.u32 t, %0, %1;\nmin.u32 t, t, %2;\nmin.u32 t, t, %3;\nsetp.eq.u32 p0, t, 0;\nmov.pred q, p0;\n"
                 POLL_EXIT("PA") POLL_LD("p0", "%0,%1,%2,%3", "%4") "bra PA;\nPA_END:\n}"
                 : V4(v) : "l"(p) : "memory");
}
__device__ __forceinline__ void poll_nz2(uint4& v, uint4& w, const uint32_t* p) {
    asm volatile("{\n.reg .pred p0, p1, q, c;\n.reg .b32 t, u, it;\n" POLL_HEAD("PB")
                 "min.u32 t, %0, %1;\nmin.u32 t, t, %2;\nmin.u32 t, t, %3;\nsetp.eq.u32 p0, t, 0;\n"
                 "min.u32 u, %4, %5;\nmin.u32 u, u, %6;\nmin.u32 u, u, %7;\nsetp.eq.u32 p1, u, 0;\nor.pred q, p0, p1;\n"
                 POLL_EXIT("PB") POLL_LD("p0", "%0,%1,%2,%3", "%8") POLL_LD("p1", "%4,%5,%6,%7", "%8+512") "bra PB;\nPB_END:\n}"
                 : V4(v), V4(w) : "l"(p) : "memory");
}
__device__ __forceinline__ void poll_nz_pair(uint32_t& v, uint32_t& w, const uint32_t* p) {
    asm volatile("{\n.reg .pred q, c;\n.reg .b32 t, it;\n" POLL_HEAD("PC")
                 "ld.relaxed.gpu.global.u32 %0, [%2];\nld.relaxed.gpu.global.u32 %1, [%2+64];\n"
                 "min.u32 t, %0, %1;\nsetp.eq.u32 q, t, 0;\n"
                 POLL_EXIT("PC") "bra PC;\nPC_END:\n}"
                 : "=&r"(v), "=&r"(w) : "l"(p) : "memory");
}
__device__ __forceinline__ void poll_nz4(uint4& a, uint4& b, uint4& c, uint4& d, const uint32_t* p) {
    asm volatile("{\n.reg .pred p0, p1, p2, p3, q, c;\n.reg .b32 t, it;\n" POLL_HEAD("PD")
                 "min.u32 t, %0, %1;\nmin.u32 t, t, %2;\nmin.u32 t, t, %3;\nsetp.eq.u32 p0, t, 0;\n"
                 "min.u32 t, %4, %5;\nmin.u32 t, t, %6;\nmin.u32 t, t, %7;\nsetp.eq.u32 p1, t, 0;\n"
                 "min.u32 t, %8, %9;\nmin.u32 t, t, %10;\nmin.u32 t, t, %11;\nsetp.eq.u32 p2, t, 0;\n"
                 "min.u32 t, %12, %13;\nmin.u32 t, t, %14;\nmin.u32 t, t, %15;\nsetp.eq.u32 p3, t, 0;\n"
                 "or.pred q, p0, p1;\nor.pred q, q, p2;\nor.pred q, q, p3;\n"
                 POLL_EXIT("PD") POLL_LD("p0", "%0,%1,%2,%3", "%16") POLL_LD("p1", "%4,%5,%6,%7", "%16+512")
                 POLL_LD("p2", "%8,%9,%10,%11", "%16+1024") POLL_LD("p3", "%12,%13,%14,%15", "%16+1536") "bra PD;\nPD_END:\n}"
                 : V4(a), V4(b), V4(c), V4(d) : "l"(p) : "memory");
}
__device__ __forceinline__ void poll_sign4(uint4& a, uint4& b, uint4& c, uint4& d, const uint32_t* p) {
    asm volatile("{\n.reg .pred p0, p1, p2, p3, q, c;\n.reg .b32 t, it;\n" POLL_HEAD("PE")
                 "lop3.b32 t, %0, %1, %2, 0x80;\nlop3.b32 t, t, %3, 0x80000000, 0x2a;\nsetp.ne.u32 p0, t, 0;\n"
                 "lop3.b32 t, %4, %5, %6, 0x80;\nlop3.b32 t, t, %7, 0x80000000, 0x2a;\nsetp.ne.u32 p1, t, 0;\n"
                 "lop3.b32 t, %8, %9, %10, 0x80;\nlop3.b32 t, t, %11, 0x80000000, 0x2a;\nsetp.ne.u32 p2, t, 0;\n"
                 "lop3.b32 t, %12, %13, %14, 0x80;\nlop3.b32 t, t, %15, 0x80000000, 0x2a;\nsetp.ne.u32 p3, t, 0;\n"
                 "or.pred q, p0, p1;\nor.pred q, q, p2;\nor.pred q, q, p3;\n"
                 POLL_EXIT("PE") POLL_LD("p0", "%0,%1,%2,%3", "%16") POLL_LD("p1", "%4,%5,%6,%7", "%16+256")
                 POLL_LD("p2", "%8,%9,%10,%11", "%16+512") POLL_LD("p3", "%12,%13,%14,%15", "%16+768") "bra PE;\nPE_END:\n}"
                 : V4(a), V4(b), V4(c), V4(d) : "l"(p) : "memory");
}

constexpr uint32_t ONES = 0x3f803f80u;

__device__ __forceinline__ void ffn1_finish(uint32_t bar, uint32_t a_w1, uint32_t a_part, uint32_t a_stat,
                                            uint32_t bias_a, uint32_t bias_b, uint32_t* dst) {
    float w0[4] = {}, w1[4] = {}, w2[4] = {}, w3[4] = {};
    mbar_wait(bar, 0);
#pragma unroll 1
    for (int s = 0; s < 28; s += 14) {
        uint4 bw[14];
#pragma unroll
        for (int i = 0; i < 14; i++) bw[i] = ldm4t(a_w1 + (s + i) * 1024);
#pragma unroll
        for (int i = 0; i < 14; i += 2) {
            mma16816(w0, ONES, ONES, ONES, ONES, bw[i].x, bw[i].y);
            mma16816(w1, ONES, ONES, ONES, ONES, bw[i].z, bw[i].w);
            mma16816(w2, ONES, ONES, ONES, ONES, bw[i + 1].x, bw[i + 1].y);
            mma16816(w3, ONES, ONES, ONES, ONES, bw[i + 1].z, bw[i + 1].w);
        }
    }
    const float cs0 = w0[0] + w2[0], cs1 = w0[1] + w2[1], cs2 = w1[0] + w3[0], cs3 = w1[1] + w3[1];
    asm volatile("barrier.sync 2, 288;" ::: "memory");
    float2 sq[7];
    float4 p[7];
#pragma unroll
    for (int w = 0; w < 7; w++) sq[w] = lds64f(a_stat + w * 64);
#pragma unroll
    for (int w = 0; w < 7; w++) p[w] = lds128f(a_part + w * 1024);
    const float sum = ((sq[0].x + sq[1].x) + (sq[2].x + sq[3].x)) + ((sq[4].x + sq[5].x) + sq[6].x);
    const float mean = sum * (1.0f / DM);
    const float msq = (((sq[0].y + sq[1].y) + (sq[2].y + sq[3].y)) + ((sq[4].y + sq[5].y) + sq[6].y)) * (1.0f / DM);
    const float var = fmaxf(fmaf(-mean, mean, msq), 0.f);
    float sd, rs;
    asm("sqrt.approx.ftz.f32 %0, %1;" : "=f"(sd) : "f"(rbf(rbf(var) + 1e-5f)));
    asm("rcp.approx.ftz.f32 %0, %1;" : "=f"(rs) : "f"(rbf(sd)));
    const float mb = rbf(fmaf(fmaf(-mean, (float)DM, sum), 1.0f / DM, mean));
    const float s0 = fmaf(-mb, cs0, ((p[0].x + p[1].x) + (p[2].x + p[3].x)) + ((p[4].x + p[5].x) + p[6].x));
    const float s1 = fmaf(-mb, cs1, ((p[0].y + p[1].y) + (p[2].y + p[3].y)) + ((p[4].y + p[5].y) + p[6].y));
    const float s2 = fmaf(-mb, cs2, ((p[0].z + p[1].z) + (p[2].z + p[3].z)) + ((p[4].z + p[5].z) + p[6].z));
    const float s3 = fmaf(-mb, cs3, ((p[0].w + p[1].w) + (p[2].w + p[3].w)) + ((p[4].w + p[5].w) + p[6].w));
    st_rlx64(dst, neg_sq_relu_bf2(add_bf2(pack_bf(s0 * rs, s1 * rs), bias_a)),
             neg_sq_relu_bf2(add_bf2(pack_bf(s2 * rs, s3 * rs), bias_b)));
}

__global__ void __launch_bounds__(NTHREADS, 1)
fused_decode_kernel(const __nv_bfloat16* __restrict__ x, const __nv_bfloat16* __restrict__ wq,
                    const __nv_bfloat16* __restrict__ b1, const __nv_bfloat16* __restrict__ b2,
                    __nv_bfloat16* __restrict__ out,
                    const __grid_constant__ CUtensorMap tm_k, const __grid_constant__ CUtensorMap tm_v,
                    const __grid_constant__ CUtensorMap tm_wo, const __grid_constant__ CUtensorMap tm_w1,
                    const __grid_constant__ CUtensorMap tm_w2) {
    extern __shared__ __align__(1024) uint8_t sp[];
    const uint32_t sb = pin(smem_u32(sp));

    const int tid = threadIdx.x, warp = tid >> 5, lane = tid & 31;
    const int g = lane >> 2, t4 = lane & 3;
    const int cta = blockIdx.x;
    const int hd = cta >> 3, bj = cta & 7;
    const bool tail = bj < 7;
    const int ri = (hd * 7 + bj) >> 1;
    const bool ffn2 = (hd + bj) & 1;
    const int bg = ri & 1, cg = ri >> 1;
    const uint32_t bar_full = sb + OFF_BAR, bar_empty = bar_full + NS * 8, bar_w = bar_empty + NS * 8;
    const uint32_t s_wq = sb + OFF_WO, s_est = sb + OFF_M + 64;

    uint32_t epoch;
    asm volatile("ld.relaxed.gpu.global.u32 %0, [%1];" : "=r"(epoch) : "l"(g_epoch[cta]) : "memory");
    uint4 xr0 = make_uint4(0, 0, 0, 0), xr1 = xr0;
    if (warp < 8) {
        if (lane < 28) {
            xr0 = ldg128_now(x + warp * DM + lane * 8);
            xr1 = ldg128_now(x + warp * DM + 224 + lane * 8);
        }
        const int row = tid >> 2, ch = tid & 3;
        const uint32_t d = s_wq + row * 64 + ((ch ^ ((row >> 1) & 3)) << 4);
        const __nv_bfloat16* p = wq + (size_t)row * (NH * DH) + cta * 32 + ch * 8;
#pragma unroll
        for (int i = 0; i < 7; i++)
            asm volatile("cp.async.cg.shared.global.L2::128B [%0], [%1], 16;"
                         :: "r"(d + i * 4096), "l"(p + (size_t)i * 64 * (NH * DH)) : "memory");
    }
    const int grp0 = (bj * NH + hd) * (SK / 8), flip = (hd & 1) * (KT / 2);
    uint64_t pol;
    asm volatile("createpolicy.fractional.L2::evict_first.b64 %0, 1.0;" : "=l"(pol));
    if (tid == 256) {
#pragma unroll
        for (int s = 0; s < D0; s++) mbar_init(bar_full + s * 8, 1);
        asm volatile("fence.mbarrier_init.release.cluster;" ::: "memory");
#pragma unroll
        for (int s = 0; s < D0; s++) {
            mbar_expect_tx(bar_full + s * 8, STAGE);
            tma_tile(sb + OFF_RING + s * STAGE, &tm_k, grp0 + (s ^ flip) * 4, bar_full + s * 8, pol);
        }
    }

    if (warp == 8) {
        if (lane == 0) {
#pragma unroll
            for (int s = D0; s < NS; s++) mbar_init(bar_full + s * 8, 1);
#pragma unroll
            for (int s = 0; s < NS; s++) mbar_init(bar_empty + s * 8, 8);
#pragma unroll
            for (int s = 0; s < 9; s++) mbar_init(bar_w + s * 8, s == 1 ? 8 : 1);
            asm volatile("fence.mbarrier_init.release.cluster;" ::: "memory");
            asm volatile("st.volatile.shared.v2.u32 [%0], {%1,%2};" :: "r"(s_est), "r"(0), "r"(clock32()) : "memory");
        }
        __syncwarp();
        asm volatile("barrier.arrive 3, 288;" ::: "memory");
        asm volatile("barrier.arrive 7, 64;" ::: "memory");
        if (lane != 0) return;
        asm volatile("prefetch.tensormap [%0];" :: "l"(&tm_v) : "memory");
        asm volatile("prefetch.tensormap [%0];" :: "l"(&tm_wo) : "memory");
        asm volatile("prefetch.tensormap [%0];" :: "l"(ffn2 ? &tm_w2 : &tm_w1) : "memory");
        uint32_t* prog = g_prog[(epoch + 1) & 1];
        uint32_t t = D0, landed = 0, pf = NS;
#pragma unroll 1
        for (int it = 0; t < NT && it < 16 * SPIN_MAX; it++) {
            if (landed < t && mbar_test(bar_full + (landed & (NS - 1)) * 8, (landed / NS) & 1)) {
                landed++;
                if (((landed + cta) & 3) == 0) asm volatile("red.relaxed.gpu.global.add.u32 [%0], 4;" :: "l"(prog) : "memory");
            }
            const uint32_t s = t & (NS - 1);
            if (t < NS) {
                if (t - landed >= D0) continue;
            } else {
                if (t == NS && pf - landed < D0 && !mbar_test(bar_empty, 0)) {
                    asm volatile("cp.async.bulk.prefetch.tensor.4d.L2.global [%0, {%1, %1, %1, %2}];"
                                 :: "l"(&tm_k), "r"(0), "r"(grp0 + (pf ^ flip) * 4) : "memory");
                    pf++;
                }
                if (t - landed >= NS) continue;
                if (t - landed >= 2) {
                    uint32_t v, c0;
                    asm volatile("ld.volatile.shared.v2.u32 {%0,%1}, [%2];" : "=r"(v), "=r"(c0) : "r"(s_est) : "memory");
                    if (t * NCTA > v + min(((clock32() - c0) * 7) >> 6, 256u) + (t - landed > 2 ? WIN : WIN + EXTRA)) continue;
                }
                if (!mbar_test(bar_empty + s * 8, (t / NS - 1) & 1)) continue;
            }
            mbar_expect_tx(bar_full + s * 8, STAGE);
            tma_tile(sb + OFF_RING + s * STAGE, t < KT ? &tm_k : &tm_v, grp0 + ((t ^ flip) & (KT - 1)) * 4, bar_full + s * 8, pol);
            t++;
        }
        asm volatile("red.relaxed.gpu.global.add.u32 [%0], %1;" :: "l"(prog), "r"(NT - ((landed + (cta & 3)) & ~3u)) : "memory");
        if (!tail) return;
        mbar_wait(bar_full + ((NT - 1 - XO) & (NS - 1)) * 8, ((NT - 1 - XO) / NS) & 1);
        mbar_expect_tx(bar_w, DH * 128);
        tma_2d(sb + OFF_WO, &tm_wo, bj * 64, hd * DH, bar_w);
        if (!ffn2) {
            mbar_wait(bar_w, 0);
            mbar_expect_tx(bar_w + 16, DM * 64);
            tma_2d(sb + OFF_W, &tm_w1, ri * 32, 0, bar_w + 16);
            tma_2d(sb + OFF_W + 224 * 64, &tm_w1, ri * 32, 224, bar_w + 16);
        } else {
            mbar_wait(bar_w + 8, 0);
#pragma unroll
            for (int i = 0; i < 7; i++) {
                mbar_expect_tx(bar_w + (2 + i) * 8, 8192);
                tma_2d(sb + OFF_RING + i * 8192, &tm_w2, cg * 16, i * 256, bar_w + (2 + i) * 8);
            }
        }
        return;
    }

    const uint32_t par = (epoch + 1) & 1;
    if (warp == 10) {
        __nanosleep(CLEAR_NS);
        const uint4 z = make_uint4(0, 0, 0, 0);
        for (int i = lane; i < MAIL_VECS; i += 32) reinterpret_cast<uint4*>(&g_mail)[cta * MAIL_VECS + i] = z;
        reinterpret_cast<uint4*>(g_q[par ^ 1])[cta * 32 + lane] = z;
        if (cta == 0 && lane == 0) { g_prog[par ^ 1][0] = 0; g_cleared[par ^ 1][0] = 0; }
        __syncwarp();
        if (lane == 0) {
            asm volatile("red.release.gpu.global.add.u32 [%0], 1;" :: "l"(g_cleared[par]) : "memory");
            uint32_t n = 0;
#pragma unroll 1
            for (int it = 0; n < NCTA && it < SPIN_MAX; it++) {
                __nanosleep(1000);
                asm volatile("ld.acquire.gpu.global.u32 %0, [%1];" : "=r"(n) : "l"(g_cleared[par]) : "memory");
            }
        }
        __syncwarp();
        asm volatile("barrier.arrive 8, 288;" ::: "memory");
        return;
    }
    const uint32_t a_w1 = pin(sb + OFF_W + (((lane >> 3) & 1) * 8 + (lane & 7)) * 64 + (((lane >> 4) ^ ((lane >> 1) & 3)) << 4));
    const uint32_t a_stat = pin(sb + OFF_D + 7168 + g * 8);

    if (warp == 9) {
        uint32_t bias_a = 0, bias_b = 0;
        if (tail && !ffn2) {
            bias_a = ldg32_now(b1 + ri * 32 + 16 + t4 * 2);
            bias_b = ldg32_now(b1 + ri * 32 + 24 + t4 * 2);
        }
        uint4 q = make_uint4(0, 0, 0, 0);
        poll_nz(q, &g_q[par][bj * (NH * DH / 2) + hd * (DH / 2) + lane * 4]);
        *reinterpret_cast<uint4*>(sp + OFF_Q + lane * 16) = q;
        asm volatile("barrier.arrive 5, 288;" ::: "memory");
        asm volatile("barrier.sync 7, 64;" ::: "memory");
        if (lane == 0) {
            uint32_t v = 0;
#pragma unroll 1
            for (int it = 0; v + WIN < (NT - 1) * NCTA && it < SPIN_MAX; it++) {
                asm volatile("ld.relaxed.gpu.global.u32 %0, [%1];" : "=r"(v) : "l"(g_prog[par]) : "memory");
                asm volatile("st.volatile.shared.v2.u32 [%0], {%1,%2};" :: "r"(s_est), "r"(v), "r"(clock32()) : "memory");
                __nanosleep(HSLEEP);
            }
        }
        __syncwarp();
        if (tail && !ffn2) {
            ffn1_finish(bar_w + 16, a_w1 ^ 32, pin(sb + OFF_D + 512 + lane * 16), a_stat, bias_a, bias_b,
                        pin(&g_mail.g[((g >> 2) * NMSG + ri * 2 + 1) * 32 + (g & 3) * 8 + (t4 ^ 1) * 2]));
        }
        return;
    }

    asm volatile("cp.async.commit_group;" ::: "memory");
    uint32_t c0w = 0, c1w = 0;
    if (!tail) {
        if (warp < 7) {
            const __nv_bfloat16* p = x + (hd >> 1) * DM + warp * 64 + (hd & 1) * 32 + ((lane >> 2) & 1) * 16 + t4 * 2;
            c0w = ldg32_now(p);
            c1w = ldg32_now(p + 8);
        }
    } else if (warp == 7) {
        if (ffn2) {
            c0w = ldg32_now(b2 + cg * 16 + (lane & 1) * 8 + (g & 6));
            c0w = __byte_perm(c0w, 0, (g & 1) ? 0x3232 : 0x1010);
        } else {
            c0w = ldg32_now(b1 + ri * 32 + t4 * 2);
            c1w = ldg32_now(b1 + ri * 32 + 8 + t4 * 2);
        }
    }

    layernorm_row(xr0, xr1, lane, sb + OFF_C + warp * (XP * 2));
    asm volatile("cp.async.wait_group 0;" ::: "memory");
    asm volatile("barrier.sync 3, 288;" ::: "memory");

    float* red_b = reinterpret_cast<float*>(sp + OFF_B);
    if (warp < 7) {
        float acc[4][4] = {};
#pragma unroll
        for (int p = 0; p < 2; p++) {
            const uint4 a = ldm4(sb + OFF_C + (lane & 7) * (XP * 2) + (warp * 64 + p * 32 + (lane >> 3) * 8) * 2);
#pragma unroll
            for (int s = 0; s < 2; s++) {
                const int row = warp * 64 + p * 32 + s * 16 + ((lane >> 3) & 1) * 8 + (lane & 7);
#pragma unroll
                for (int np = 0; np < 2; np++) {
                    const int ch = np * 2 + (lane >> 4);
                    const uint4 bw = ldm4t(s_wq + row * 64 + ((ch ^ ((row >> 1) & 3)) << 4));
                    mma16816(acc[np * 2], s ? a.z : a.x, 0, s ? a.w : a.y, 0, bw.x, bw.y);
                    mma16816(acc[np * 2 + 1], s ? a.z : a.x, 0, s ? a.w : a.y, 0, bw.z, bw.w);
                }
            }
        }
#pragma unroll
        for (int n = 0; n < 4; n++)
            *reinterpret_cast<float2*>(red_b + (warp * 8 + g) * 40 + n * 8 + t4 * 2) = make_float2(acc[n][0], acc[n][1]);
    }
    asm volatile("fence.proxy.async.shared::cta;" ::: "memory");
    cbar();
    if (tid < 128) {
        const int b = tid >> 4, wd = tid & 15;
        float s0 = 0.f, s1 = 0.f;
#pragma unroll
        for (int w = 0; w < 7; w++) {
            const float2 p = *reinterpret_cast<const float2*>(red_b + (w * 8 + b) * 40 + wd * 2);
            s0 += p.x; s1 += p.y;
        }
        st_rlx32(&g_q[par][b * (NH * DH / 2) + cta * 16 + (wd & 3) * 4 + ((wd >> 2) & 1) * 2 + (wd >> 3)], enc(pack_bf(s0, s1)));
    }

    uint32_t* const p_o_st = pin(&g_mail.o[(hd * 8 + warp) * 128 + bj * 16 + t4 * 4]);
    const uint32_t* const p_o_ld = pin(&g_mail.o[(hd * 8 + warp) * 128 + lane * 4]);
    uint32_t* const p_p2_st = pin(g_mail.p2 + ((bj * 16 + warp * 2 + (lane >> 4)) * 16 + hd) * 32 + (lane & 15) * 2);
    const uint32_t* p_in;
    uint32_t* p_res;
    if (!tail) {
        p_in = g_mail.p2 + ((warp * 16 + hd) * 16 + (lane >> 3)) * 32 + (lane & 7) * 4;
        p_res = &g_mail.h[(lane >> 3) % HREP][(warp * 2 + (hd & 1)) * 128 + (hd >> 1) * 16 + t4 * 4 + ((lane >> 2) & 1) * 2];
    } else if (!ffn2) {
        p_in = &g_mail.h[ri % HREP][warp * 256 + lane * 4];
        p_res = &g_mail.g[((g >> 2) * NMSG + ri * 2) * 32 + (g & 3) * 8 + t4 * 2];
    } else {
        const int b = bg * 4 + (lane & 2);
        p_in = warp < 7 ? &g_mail.g[(bg * NMSG + warp * 16 + (g >> 2) * 8 + (t4 >> 1)) * 32 + (g & 3) * 8 + (t4 & 1) * 4]
                        : &g_mail.h[ri % HREP][(cg >> 1) * 128 + b * 16 + (g >> 1) * 4 + (cg & 1) * 2 + (lane & 1)];
        p_res = reinterpret_cast<uint32_t*>(out + b * DM + cg * 16 + (lane & 1) * 8 + g);
    }
    p_in = pin(p_in);
    p_res = pin(p_res);
    const uint32_t a_wo = pin(sb + OFF_WO + (warp * 32 + (lane >> 4) * 8 + (lane & 7)) * 128 + ((((lane >> 3) & 1) ^ (lane & 7)) << 4));
    const uint32_t a_r2w = pin(sb + OFF_B + warp * 2048 + (t4 * 8 + ((g + 2 * t4) & 7)) * 16);
    const uint32_t a_r2r = pin(sb + OFF_B + (lane >> 3) * 512 +
                               ((warp >> 1) * 8 + ((lane + (warp & 6)) & 7)) * 16 + ((warp ^ (lane >> 3)) & 1) * 8);
    __nv_bfloat16* sc = reinterpret_cast<__nv_bfloat16*>(sp + OFF_A);

    float mx = -INFINITY;
    {
        uint4 q[8];
        asm volatile("barrier.sync 5, 288;" ::: "memory");
#pragma unroll
        for (int i = 0; i < 8; i++) q[i] = lds128(sb + OFF_Q + i * 64 + t4 * 16);
        const uint32_t ka = pin(sb + OFF_RING + (warp & 3) * 4096 + (lane & 7) * 128 + (((lane >> 3) ^ (lane & 7)) << 4));
        uint32_t* scw = reinterpret_cast<uint32_t*>(sc) + t4 * 4 + (warp & 1) * 2 + ((warp >> 1) & 1);
#pragma unroll 1
        for (int t = warp >> 2; t < KT; t += 2) {
            const int st = t & (NS - 1);
            mbar_wait(bar_full + st * 8, (t / NS) & 1);
            uint4 kf[8];
#pragma unroll
            for (int i = 0; i < 8; i++) kf[i] = ldm4((ka ^ ((i & 1) << 6)) + st * STAGE + (i >> 1) * 1024);
            float c[4][4] = {};
#pragma unroll
            for (int i = 0; i < 8; i++) {
                mma16816(c[(i & 1) * 2], q[i].x, q[i].y, q[i].z, q[i].w, kf[i].x, kf[i].y);
                mma16816(c[(i & 1) * 2 + 1], q[i].x, q[i].y, q[i].z, q[i].w, kf[i].z, kf[i].w);
            }
            __syncwarp();
            if (lane == 0) mbar_arrive2(bar_empty + st * 8);
            const uint32_t d = pack_bf((c[0][0] + c[2][0]) + (c[1][2] + c[3][2]), (c[0][1] + c[2][1]) + (c[1][3] + c[3][3]));
            const uint32_t sw = pack_bf(bf_lo(d) * 0.0625f, bf_hi(d) * 0.0625f);
            mx = fmaxf(mx, fmaxf(bf_lo(sw), bf_hi(sw)));
            if (lane < 4) scw[t * 16] = sw;
        }
    }

    {
        float* sm_m = reinterpret_cast<float*>(sp + OFF_M);
        mx = fmaxf(mx, __shfl_xor_sync(0xffffffffu, mx, 1));
        mx = fmaxf(mx, __shfl_xor_sync(0xffffffffu, mx, 2));
        if (lane == 0) sm_m[warp] = mx;
        cbar();
#pragma unroll
        for (int w = 0; w < 8; w++) mx = fmaxf(mx, sm_m[w]);
        float e[16], sum = 0.f;
#pragma unroll
        for (int i = 0; i < 4; i++) {
            const uint2 s = *reinterpret_cast<const uint2*>(sc + i * 1024 + tid * 4);
            e[i * 4 + 0] = expf(bf_lo(s.x) - mx); e[i * 4 + 1] = expf(bf_hi(s.x) - mx);
            e[i * 4 + 2] = expf(bf_lo(s.y) - mx); e[i * 4 + 3] = expf(bf_hi(s.y) - mx);
            sum += (e[i * 4] + e[i * 4 + 1]) + (e[i * 4 + 2] + e[i * 4 + 3]);
        }
        sum = warp_sum(sum);
        if (lane == 0) sm_m[8 + warp] = sum;
        cbar();
        sum = 0.f;
#pragma unroll
        for (int w = 0; w < 8; w++) sum += sm_m[8 + w];
        const float inv = 1.0f / sum;
#pragma unroll
        for (int i = 0; i < 4; i++)
            *reinterpret_cast<uint2*>(sc + i * 1024 + tid * 4) =
                make_uint2(pack_bf(e[i * 4] * inv, e[i * 4 + 1] * inv), pack_bf(e[i * 4 + 2] * inv, e[i * 4 + 3] * inv));
        asm volatile("barrier.sync 8, 288;" ::: "memory");
    }
    if (tid == 0) st_rlx32(g_epoch[cta], epoch + 1);

    uint4 ov = make_uint4(0, 0, 0, 0);
    {
        float oa[4][4] = {}, ob[4][4] = {};
        const uint32_t va = pin(sb + OFF_RING + ((lane >> 3) & 1) * 4096 + (warp >> 1) * 1024 + (lane & 7) * 128 +
                                ((((warp & 1) * 4 + (lane >> 4)) ^ (lane & 7)) << 4));
        auto pv_tile = [&](int t) {
            const int st = t & (NS - 1);
            const uint4 p = lds128(sb + OFF_A + t * 64 + t4 * 16);
            const uint32_t va0 = pin(va + st * STAGE), va1 = pin(va0 ^ 32);
            mbar_wait(bar_full + st * 8, ((KT + t) / NS) & 1);
            const uint4 v0 = ldm4t(va0), v1 = ldm4t(va1), v2 = ldm4t(va0 + 8192), v3 = ldm4t(va1 + 8192);
            mma16816(oa[0], p.x, p.y, p.z, p.w, v0.x, v0.y);
            mma16816(oa[1], p.x, p.y, p.z, p.w, v0.z, v0.w);
            mma16816(oa[2], p.x, p.y, p.z, p.w, v1.x, v1.y);
            mma16816(oa[3], p.x, p.y, p.z, p.w, v1.z, v1.w);
            mma16816(ob[0], p.x, p.y, p.z, p.w, v2.x, v2.y);
            mma16816(ob[1], p.x, p.y, p.z, p.w, v2.z, v2.w);
            mma16816(ob[2], p.x, p.y, p.z, p.w, v3.x, v3.y);
            mma16816(ob[3], p.x, p.y, p.z, p.w, v3.z, v3.w);
            __syncwarp();
            if (lane == 0) mbar_arrive(bar_empty + st * 8);
        };
#pragma unroll 1
        for (int t = 0; t < KT - OEARLY; t++) pv_tile(t);
        ld_rlx128_if(tail, ov, p_o_ld);
#pragma unroll 1
        for (int t = KT - OEARLY; t < KT; t++) pv_tile(t);
        st_rlx128_if(lane < 4, p_o_st,
                     enc(pack_bf(oa[0][0] + ob[0][2], oa[0][1] + ob[0][3])), enc(pack_bf(oa[1][0] + ob[1][2], oa[1][1] + ob[1][3])),
                     enc(pack_bf(oa[2][0] + ob[2][2], oa[2][1] + ob[2][3])), enc(pack_bf(oa[3][0] + ob[3][2], oa[3][1] + ob[3][3])));
    }

    if (!tail) {
        if (warp < 7) {
            uint4 v0 = make_uint4(0, 0, 0, 0), v1 = v0, v2 = v0, v3 = v0;
            poll_nz4(v0, v1, v2, v3, p_in);
            float a0 = (__uint_as_float(v0.x) + __uint_as_float(v1.x)) + (__uint_as_float(v2.x) + __uint_as_float(v3.x));
            float a1 = (__uint_as_float(v0.y) + __uint_as_float(v1.y)) + (__uint_as_float(v2.y) + __uint_as_float(v3.y));
            float a2 = (__uint_as_float(v0.z) + __uint_as_float(v1.z)) + (__uint_as_float(v2.z) + __uint_as_float(v3.z));
            float a3 = (__uint_as_float(v0.w) + __uint_as_float(v1.w)) + (__uint_as_float(v2.w) + __uint_as_float(v3.w));
#pragma unroll
            for (int o = 8; o <= 16; o <<= 1) {
                a0 += __shfl_xor_sync(0xffffffffu, a0, o);
                a1 += __shfl_xor_sync(0xffffffffu, a1, o);
                a2 += __shfl_xor_sync(0xffffffffu, a2, o);
                a3 += __shfl_xor_sync(0xffffffffu, a3, o);
            }
            st_rlx64_if(lane < 8 * HREP, p_res, enc(add_bf2(c0w, pack_bf(a0, a2))), enc(add_bf2(c1w, pack_bf(a1, a3))));
        }
        return;
    }

    {
        uint4 v = ov;
        ld_rlx128_if(min(min(v.x, v.y), min(v.z, v.w)) == 0, v, p_o_ld);
        mbar_wait(bar_w, 0);
        uint4 a[2][4];
#pragma unroll
        for (int s = 0; s < 2; s++)
#pragma unroll
            for (int mt = 0; mt < 4; mt++) a[s][mt] = ldm4t((a_wo ^ (mt << 5)) + s * 2048);
        poll_nz(v, p_o_ld);
        float acc[4][4] = {};
#pragma unroll
        for (int mt = 0; mt < 4; mt++) mma16816(acc[mt], a[0][mt].x, a[0][mt].y, a[0][mt].z, a[0][mt].w, v.x, v.y);
#pragma unroll
        for (int mt = 0; mt < 4; mt++) mma16816(acc[mt], a[1][mt].x, a[1][mt].y, a[1][mt].z, a[1][mt].w, v.z, v.w);
#pragma unroll
        for (int mt = 0; mt < 4; mt += 2) {
            sts128(a_r2w + mt * 512, acc[mt][0], acc[mt][2], acc[mt][1], acc[mt][3]);
            sts128(a_r2w + mt * 512 + 512, acc[mt + 1][1], acc[mt + 1][3], acc[mt + 1][0], acc[mt + 1][2]);
        }
        cbar();
        float2 p[8];
#pragma unroll
        for (int w = 0; w < 8; w++) p[w] = lds64f(a_r2r + w * 2048);
        const float s0 = ((p[0].x + p[1].x) + (p[2].x + p[3].x)) + ((p[4].x + p[5].x) + (p[6].x + p[7].x));
        const float s1 = ((p[0].y + p[1].y) + (p[2].y + p[3].y)) + ((p[4].y + p[5].y) + (p[6].y + p[7].y));
        st_rlx64(p_p2_st, enc(__float_as_uint(s0)), enc(__float_as_uint(s1)));
        if (lane == 0) asm volatile("mbarrier.arrive.relaxed.cta.shared.b64 _, [%0];" :: "r"(bar_w + 8) : "memory");
    }

    if (!ffn2) {
        if (warp < 7) {
            uint4 v0 = ld_rlx128(p_in), v1 = ld_rlx128(p_in + 128);
            const uint32_t a_part = pin(sb + OFF_D + warp * 1024 + lane * 16);
            mbar_wait(bar_w + 16, 0);
            uint4 bw[4][2];
#pragma unroll
            for (int s = 0; s < 4; s++) {
                bw[s][0] = ldm4t(a_w1 + warp * 4096 + s * 1024);
                bw[s][1] = ldm4t((a_w1 ^ 32) + warp * 4096 + s * 1024);
            }
            poll_nz2(v0, v1, p_in);
            const uint32_t hw[8] = {v0.x, v0.y, v0.z, v0.w, v1.x, v1.y, v1.z, v1.w};
            float c[4][4] = {}, cs[4] = {};
#pragma unroll
            for (int s = 0; s < 4; s++) {
                mma16816(cs, hw[2 * s], ONES, hw[2 * s + 1], ONES, hw[2 * s], hw[2 * s + 1]);
                mma16816(c[0], hw[2 * s], ONES, hw[2 * s + 1], ONES, bw[s][0].x, bw[s][0].y);
                mma16816(c[1], hw[2 * s], ONES, hw[2 * s + 1], ONES, bw[s][0].z, bw[s][0].w);
                mma16816(c[2], hw[2 * s], ONES, hw[2 * s + 1], ONES, bw[s][1].x, bw[s][1].y);
                mma16816(c[3], hw[2 * s], ONES, hw[2 * s + 1], ONES, bw[s][1].z, bw[s][1].w);
            }
            if (t4 == (g >> 1)) sts64(a_stat + warp * 64, (g & 1) ? cs[3] : cs[2], (g & 1) ? cs[1] : cs[0]);
            sts128(a_part, c[0][0], c[0][1], c[1][0], c[1][1]);
            sts128(a_part + 512, c[2][0], c[2][1], c[3][0], c[3][1]);
            asm volatile("barrier.arrive 2, 288;" ::: "memory");
        } else {
            ffn1_finish(bar_w + 16, a_w1, pin(sb + OFF_D + lane * 16), a_stat, c0w, c1w, p_res);
        }
    } else if (warp < 7) {
        const uint32_t a0 = pin(sb + OFF_RING + warp * 8192 +
                                (((lane >> 2) & 1) * 18 + (lane >> 4) * 8 + ((lane >> 1) & 1) * 4 + (lane & 1)) * 32 +
                                ((((lane >> 3) ^ (lane >> 1)) & 1) << 4));
        const uint32_t a_r5 = pin(sb + OFF_D + warp * 256 + (t4 >> 1) * 1856 + (g * 2 + (t4 & 1)) * 16);
        mbar_wait(bar_w + (2 + warp) * 8, 0);
        uint4 aw[2][8];
#pragma unroll
        for (int hh = 0; hh < 2; hh++)
#pragma unroll
            for (int s = 0; s < 8; s++) aw[hh][s] = ldm4t((a0 ^ ((s & 1) << 6)) + hh * 4096 + (s >> 1) * 1024);
        asm volatile("barrier.sync 6, 256;" ::: "memory");
        uint4 u[4];
#pragma unroll
        for (int i = 0; i < 4; i++) u[i] = ld_rlx128(p_in + i * 64);
        poll_sign4(u[0], u[1], u[2], u[3], p_in);
        float y[2][2][4] = {};
#pragma unroll
        for (int i = 0; i < 4; i++)
#pragma unroll
            for (int hh = 0; hh < 2; hh++) {
                mma16816(y[hh][0], aw[hh][2 * i].x, aw[hh][2 * i].y, aw[hh][2 * i].z, aw[hh][2 * i].w, u[i].x, u[i].y);
                mma16816(y[hh][1], aw[hh][2 * i + 1].x, aw[hh][2 * i + 1].y, aw[hh][2 * i + 1].z, aw[hh][2 * i + 1].w, u[i].z, u[i].w);
            }
        const bool lo = t4 < 2;
        sts128(a_r5, lo ? y[0][0][0] + y[0][1][0] : y[1][0][0] + y[1][1][0], lo ? y[0][0][1] + y[0][1][1] : y[1][0][1] + y[1][1][1],
               lo ? y[0][0][2] + y[0][1][2] : y[1][0][2] + y[1][1][2], lo ? y[0][0][3] + y[0][1][3] : y[1][0][3] + y[1][1][3]);
        asm volatile("barrier.arrive 4, 256;" ::: "memory");
    } else {
        uint32_t h0, h1;
        poll_nz_pair(h0, h1, p_in);
        asm volatile("barrier.arrive 6, 256;" ::: "memory");
        const uint32_t hres = __byte_perm(h0, h1, (g & 1) ? 0x7632 : 0x5410);
        const uint32_t a_r5 = pin(sb + OFF_D + lane * 8);
        asm volatile("barrier.sync 4, 256;" ::: "memory");
        float2 y[14];
#pragma unroll
        for (int w = 0; w < 14; w++) y[w] = lds64f(a_r5 + w * 256 + (w >= 7 ? 64 : 0));
        const float y0 = (((y[0].x + y[1].x) + (y[2].x + y[3].x)) + ((y[4].x + y[5].x) + (y[6].x + y[7].x))) +
                         (((y[8].x + y[9].x) + (y[10].x + y[11].x)) + (y[12].x + y[13].x));
        const float y1 = (((y[0].y + y[1].y) + (y[2].y + y[3].y)) + ((y[4].y + y[5].y) + (y[6].y + y[7].y))) +
                         (((y[8].y + y[9].y) + (y[10].y + y[11].y)) + (y[12].y + y[13].y));
        const uint32_t res = add_bf2(hres, add_bf2(pack_bf(-y0, -y1), c0w));
        asm volatile("st.global.u16 [%0], %1;" :: "l"(p_res), "h"((uint16_t)res) : "memory");
        asm volatile("st.global.u16 [%0+%2], %1;" :: "l"(p_res), "h"((uint16_t)(res >> 16)), "n"(DM * 2) : "memory");
    }
}

typedef CUresult (*EncodeTiledFn)(CUtensorMap*, CUtensorMapDataType, cuuint32_t, void*, const cuuint64_t*,
                                  const cuuint64_t*, const cuuint32_t*, const cuuint32_t*, CUtensorMapInterleave,
                                  CUtensorMapSwizzle, CUtensorMapL2promotion, CUtensorMapFloatOOBfill);

void encode_2d(EncodeTiledFn fn, CUtensorMap* tm, void* base, int rows, int cols, int box_rows, int box_cols,
               CUtensorMapSwizzle sw) {
    cuuint64_t dims[2] = {(cuuint64_t)cols, (cuuint64_t)rows};
    cuuint64_t strides[1] = {(cuuint64_t)cols * 2};
    cuuint32_t box[2] = {(cuuint32_t)box_cols, (cuuint32_t)box_rows};
    cuuint32_t es[2] = {1, 1};
    fn(tm, CU_TENSOR_MAP_DATA_TYPE_BFLOAT16, 2, base, dims, strides, box, es, CU_TENSOR_MAP_INTERLEAVE_NONE, sw,
       CU_TENSOR_MAP_L2_PROMOTION_L2_128B, CU_TENSOR_MAP_FLOAT_OOB_FILL_NONE);
}

void encode_kv(EncodeTiledFn fn, CUtensorMap* tm, void* base) {
    cuuint64_t dims[4] = {64, 8, 4, (cuuint64_t)NB * NH * SK / 8};
    cuuint64_t strides[3] = {DH * 2, 128, 8 * DH * 2};
    cuuint32_t box[4] = {64, 8, 4, TILE_KEYS / 8};
    cuuint32_t es[4] = {1, 1, 1, 1};
    fn(tm, CU_TENSOR_MAP_DATA_TYPE_BFLOAT16, 4, base, dims, strides, box, es, CU_TENSOR_MAP_INTERLEAVE_NONE,
       CU_TENSOR_MAP_SWIZZLE_128B, CU_TENSOR_MAP_L2_PROMOTION_NONE, CU_TENSOR_MAP_FLOAT_OOB_FILL_NONE);
}

}

extern "C" void kernel_launch(void* const* d_in, const int* in_sizes, int n_in, void* d_out, int out_size) {
    (void)in_sizes; (void)n_in; (void)out_size;
    static EncodeTiledFn encode = nullptr;
    if (!encode) {
        void* fn = nullptr;
        cudaDriverEntryPointQueryResult qr;
        cudaGetDriverEntryPoint("cuTensorMapEncodeTiled", &fn, cudaEnableDefault, &qr);
        encode = (EncodeTiledFn)fn;
        cudaFuncSetAttribute(fused_decode_kernel, cudaFuncAttributeMaxDynamicSharedMemorySize, SMEM_BYTES);
    }
    CUtensorMap tm_k, tm_v, tm_wo, tm_w1, tm_w2;
    encode_kv(encode, &tm_k, d_in[1]);
    encode_kv(encode, &tm_v, d_in[2]);
    encode_2d(encode, &tm_wo, d_in[4], NH * DH, DM, 256, 64, CU_TENSOR_MAP_SWIZZLE_128B);
    encode_2d(encode, &tm_w1, d_in[6], DM, FF, 224, 32, CU_TENSOR_MAP_SWIZZLE_64B);
    encode_2d(encode, &tm_w2, d_in[8], FF, DM, 256, 16, CU_TENSOR_MAP_SWIZZLE_32B);
    fused_decode_kernel<<<NCTA, NTHREADS, SMEM_BYTES, cudaStreamPerThread>>>(
        (const __nv_bfloat16*)d_in[0], (const __nv_bfloat16*)d_in[3], (const __nv_bfloat16*)d_in[7],
        (const __nv_bfloat16*)d_in[9], (__nv_bfloat16*)d_out, tm_k, tm_v, tm_wo, tm_w1, tm_w2);
}
```

```cpp
#include <cuda_runtime.h>
#include <cuda_bf16.h>
#include <cuda.h>
#include <stdint.h>

namespace {

constexpr int NB = 8, DM = 448, NH = 16, SK = 4096, DH = 256, FF = 1792;
constexpr int NCTA = NB * NH;
constexpr int NMSG = FF / 16;
constexpr int TILE_KEYS = 32;
constexpr int STAGE = TILE_KEYS * DH * 2;
constexpr int NS = 8;
constexpr int KT = SK / TILE_KEYS;
constexpr int NT = 2 * KT;
constexpr int NTHREADS = 352;
constexpr int XP = 456;
constexpr int SPIN_MAX = 1 << 22;

constexpr int D0 = 3;
constexpr int WIN = 416;
constexpr int EXTRA = 192;
constexpr int HSLEEP = 300;
constexpr int XO = 1;
constexpr int OEARLY = 3;
constexpr int HREP = 2;
constexpr int CLEAR_NS = 8000;

constexpr int OFF_RING = 0;
constexpr int OFF_WO = OFF_RING + NS * STAGE;
constexpr int OFF_W = OFF_WO + DH * 128;
constexpr int OFF_A = OFF_W + DM * 64;
constexpr int OFF_B = OFF_A + SK * 2;
constexpr int OFF_Q = OFF_B + 8960;
constexpr int OFF_C = OFF_Q + 512;
constexpr int OFF_D = OFF_C + NB * XP * 2;
constexpr int OFF_M = OFF_D + 7680;
constexpr int OFF_BAR = OFF_M + 128;
constexpr int SMEM_BYTES = OFF_BAR + (2 * NS + 9) * 8;
static_assert(SMEM_BYTES <= 232448, "shared memory budget");
static_assert(OFF_D - OFF_B >= 16384, "the wo reduction reuses the prologue areas");

struct __align__(128) Mail {
    uint32_t o[NH * NB * DH / 2];
    uint32_t p2[7 * 16 * 16 * 32];
    uint32_t h[HREP][NB * DM / 2];
    uint32_t g[2 * NMSG * 32];
};
struct __align__(128) Scratch {
    uint32_t epoch[NCTA][32];
    uint32_t prog[2][32];
    uint32_t cleared[2][32];
    uint32_t q[2][NB * NH * DH / 2];
    Mail mail;
};
__device__ Scratch g_scratch;
constexpr int MAIL_VECS = sizeof(Mail) / 16 / NCTA;
static_assert(sizeof(Mail) % (16 * NCTA) == 0, "equal shares");

__device__ __forceinline__ uint32_t smem_u32(const void* p) { return (uint32_t)__cvta_generic_to_shared(p); }

__device__ __forceinline__ void mbar_init(uint32_t a, uint32_t c) {
    asm volatile("mbarrier.init.shared.b64 [%0], %1;" :: "r"(a), "r"(c) : "memory");
}
__device__ __forceinline__ void mbar_expect_tx(uint32_t a, uint32_t bytes) {
    asm volatile("mbarrier.arrive.expect_tx.shared.b64 _, [%0], %1;" :: "r"(a), "r"(bytes) : "memory");
}
__device__ __forceinline__ void mbar_arrive(uint32_t a) {
    asm volatile("mbarrier.arrive.shared.b64 _, [%0];" :: "r"(a) : "memory");
}
__device__ __forceinline__ void mbar_arrive2(uint32_t a) {
    asm volatile("mbarrier.arrive.shared.b64 _, [%0], 2;" :: "r"(a) : "memory");
}
__device__ __forceinline__ bool mbar_test(uint32_t a, uint32_t parity) {
    uint32_t ok;
    asm volatile("{\n.reg .pred p;\nmbarrier.test_wait.parity.shared.b64 p, [%1], %2;\nselp.u32 %0, 1, 0, p;\n}"
                 : "=r"(ok) : "r"(a), "r"(parity) : "memory");
    return ok;
}
__device__ __forceinline__ uint32_t clock32() {
    uint32_t c;
    asm volatile("mov.u32 %0, %%clock;" : "=r"(c));
    return c;
}
__device__ __forceinline__ void mbar_wait(uint32_t a, uint32_t parity) {
    uint32_t ok;
    int it = 0;
    do {
        asm volatile("{\n.reg .pred p;\nmbarrier.try_wait.parity.shared.b64 p, [%1], %2;\nselp.u32 %0, 1, 0, p;\n}"
                     : "=r"(ok) : "r"(a), "r"(parity) : "memory");
    } while (!ok && ++it < SPIN_MAX);
    if (!ok) __trap();
}
__device__ __forceinline__ void tma_tile(uint32_t dst, const CUtensorMap* tm, int group, uint32_t bar, uint64_t pol) {
    asm volatile("cp.async.bulk.tensor.4d.shared::cluster.global.mbarrier::complete_tx::bytes.L2::cache_hint"
                 " [%0], [%1, {%3, %3, %3, %4}], [%2], %5;"
                 :: "r"(dst), "l"(tm), "r"(bar), "r"(0), "r"(group), "l"(pol) : "memory");
}
__device__ __forceinline__ void tma_2d(uint32_t dst, const CUtensorMap* tm, int c0, int c1, uint32_t bar) {
    asm volatile("cp.async.bulk.tensor.2d.shared::cluster.global.mbarrier::complete_tx::bytes [%0], [%1, {%3, %4}], [%2];"
                 :: "r"(dst), "l"(tm), "r"(bar), "r"(c0), "r"(c1) : "memory");
}
__device__ __forceinline__ void cbar() { asm volatile("barrier.sync 1, 256;" ::: "memory"); }

__device__ __forceinline__ uint4 lds128(uint32_t a) {
    uint4 v;
    asm volatile("ld.shared.v4.u32 {%0,%1,%2,%3}, [%4];" : "=r"(v.x), "=r"(v.y), "=r"(v.z), "=r"(v.w) : "r"(a) : "memory");
    return v;
}
__device__ __forceinline__ uint4 ldm4(uint32_t a) {
    uint4 v;
    asm volatile("ldmatrix.sync.aligned.m8n8.x4.shared.b16 {%0,%1,%2,%3}, [%4];"
                 : "=r"(v.x), "=r"(v.y), "=r"(v.z), "=r"(v.w) : "r"(a) : "memory");
    return v;
}
__device__ __forceinline__ uint4 ldm4t(uint32_t a) {
    uint4 v;
    asm volatile("ldmatrix.sync.aligned.m8n8.x4.trans.shared.b16 {%0,%1,%2,%3}, [%4];"
                 : "=r"(v.x), "=r"(v.y), "=r"(v.z), "=r"(v.w) : "r"(a) : "memory");
    return v;
}
__device__ __forceinline__ void mma16816(float (&c)[4], uint32_t a0, uint32_t a1, uint32_t a2, uint32_t a3, uint32_t b0, uint32_t b1) {
    asm volatile("mma.sync.aligned.m16n8k16.row.col.f32.bf16.bf16.f32 {%0,%1,%2,%3}, {%4,%5,%6,%7}, {%8,%9}, {%0,%1,%2,%3};"
                 : "+f"(c[0]), "+f"(c[1]), "+f"(c[2]), "+f"(c[3])
                 : "r"(a0), "r"(a1), "r"(a2), "r"(a3), "r"(b0), "r"(b1));
}
__device__ __forceinline__ uint4 ld_rlx128(const uint32_t* p) {
    uint4 v;
    asm volatile("ld.relaxed.gpu.global.v4.u32 {%0,%1,%2,%3}, [%4];" : "=r"(v.x), "=r"(v.y), "=r"(v.z), "=r"(v.w) : "l"(p) : "memory");
    return v;
}
__device__ __forceinline__ void ld_rlx128_if(bool c, uint4& v, const uint32_t* p) {
    asm volatile("{\n.reg .pred p;\nsetp.ne.u32 p, %5, 0;\n@p ld.relaxed.gpu.global.v4.u32 {%0,%1,%2,%3}, [%4];\n}"
                 : "+r"(v.x), "+r"(v.y), "+r"(v.z), "+r"(v.w) : "l"(p), "r"((uint32_t)c) : "memory");
}
__device__ __forceinline__ uint32_t ldg32_now(const void* p) {
    uint32_t v;
    asm volatile("ld.global.nc.u32 %0, [%1];" : "=r"(v) : "l"(p) : "memory");
    return v;
}
__device__ __forceinline__ uint4 ldg128_now(const void* p) {
    uint4 v;
    asm volatile("ld.global.nc.v4.u32 {%0,%1,%2,%3}, [%4];" : "=r"(v.x), "=r"(v.y), "=r"(v.z), "=r"(v.w) : "l"(p) : "memory");
    return v;
}
__device__ __forceinline__ void st_rlx32(uint32_t* p, uint32_t v) {
    asm volatile("st.relaxed.gpu.global.u32 [%0], %1;" :: "l"(p), "r"(v) : "memory");
}
__device__ __forceinline__ void st_rlx64(uint32_t* p, uint32_t a, uint32_t b) {
    asm volatile("st.relaxed.gpu.global.v2.u32 [%0], {%1,%2};" :: "l"(p), "r"(a), "r"(b) : "memory");
}

__device__ __forceinline__ void st_rlx64_if(bool c, uint32_t* p, uint32_t a, uint32_t b) {
    asm volatile("{\n.reg .pred p;\nsetp.ne.u32 p, %3, 0;\n@p st.relaxed.gpu.global.v2.u32 [%0], {%1,%2};\n}"
                 :: "l"(p), "r"(a), "r"(b), "r"((uint32_t)c) : "memory");
}

__device__ __forceinline__ void st_rlx128_if(bool c, uint32_t* p, uint32_t a, uint32_t b, uint32_t d, uint32_t e) {
    asm volatile("{\n.reg .pred p;\nsetp.ne.u32 p, %5, 0;\n@p st.relaxed.gpu.global.v4.u32 [%0], {%1,%2,%3,%4};\n}"
                 :: "l"(p), "r"(a), "r"(b), "r"(d), "r"(e), "r"((uint32_t)c) : "memory");
}
__device__ __forceinline__ float bf_lo(uint32_t w) { return __uint_as_float(w << 16); }
__device__ __forceinline__ float bf_hi(uint32_t w) { return __uint_as_float(w & 0xffff0000u); }
__device__ __forceinline__ uint32_t pack_bf(float lo, float hi) {
    __nv_bfloat162 v = __floats2bfloat162_rn(lo, hi);
    return *reinterpret_cast<uint32_t*>(&v);
}
__device__ __forceinline__ float rbf(float x) { return __uint_as_float(pack_bf(0.f, x)); }
__device__ __forceinline__ uint32_t enc(uint32_t w) { return w ? w : 0x80000000u; }

__device__ __forceinline__ float warp_sum(float v) {
#pragma unroll
    for (int o = 16; o > 0; o >>= 1) v += __shfl_xor_sync(0xffffffffu, v, o);
    return v;
}

__device__ __forceinline__ void layernorm_row(const uint4& r0, const uint4& r1, int lane, uint32_t dst_row) {
    const bool act = lane < 28;
    float v[16];
    const uint32_t w[8] = {r0.x, r0.y, r0.z, r0.w, r1.x, r1.y, r1.z, r1.w};
#pragma unroll
    for (int i = 0; i < 8; i++) { v[2 * i] = act ? bf_lo(w[i]) : 0.f; v[2 * i + 1] = act ? bf_hi(w[i]) : 0.f; }
    float s = 0.f;
#pragma unroll
    for (int i = 0; i < 16; i++) s += v[i];
    const float mean = warp_sum(s) / DM;
    float q = 0.f;
#pragma unroll
    for (int i = 0; i < 16; i++) { const float d = v[i] - mean; q = fmaf(d, d, q); }
    const float var = warp_sum(act ? q : 0.f) / DM;
    const float mb = rbf(mean);
    const float sd = rbf(sqrtf(rbf(rbf(var) + 1e-5f)));
    const float rs = 1.0f / sd;
    uint32_t o[8];
#pragma unroll
    for (int i = 0; i < 8; i++) o[i] = pack_bf(rbf(v[2 * i] - mb) * rs, rbf(v[2 * i + 1] - mb) * rs);
    if (act) {
        asm volatile("st.shared.v4.u32 [%0], {%1,%2,%3,%4};" :: "r"(dst_row + lane * 16), "r"(o[0]), "r"(o[1]), "r"(o[2]), "r"(o[3]) : "memory");
        asm volatile("st.shared.v4.u32 [%0], {%1,%2,%3,%4};" :: "r"(dst_row + 448 + lane * 16), "r"(o[4]), "r"(o[5]), "r"(o[6]), "r"(o[7]) : "memory");
    }
}

template <class T> __device__ __forceinline__ T* pin(T* p) { asm volatile("" : "+l"(p)); return p; }
__device__ __forceinline__ uint32_t pin(uint32_t v) { asm volatile("" : "+r"(v)); return v; }
__device__ __forceinline__ void sts64(uint32_t a, float x, float y) {
    asm volatile("st.shared.v2.f32 [%0], {%1,%2};" :: "r"(a), "f"(x), "f"(y) : "memory");
}
__device__ __forceinline__ void sts128(uint32_t a, float x, float y, float z, float w) {
    asm volatile("st.shared.v4.f32 [%0], {%1,%2,%3,%4};" :: "r"(a), "f"(x), "f"(y), "f"(z), "f"(w) : "memory");
}
__device__ __forceinline__ float2 lds64f(uint32_t a) {
    float2 v;
    asm volatile("ld.shared.v2.f32 {%0,%1}, [%2];" : "=f"(v.x), "=f"(v.y) : "r"(a) : "memory");
    return v;
}
__device__ __forceinline__ float4 lds128f(uint32_t a) {
    float4 v;
    asm volatile("ld.shared.v4.f32 {%0,%1,%2,%3}, [%4];" : "=f"(v.x), "=f"(v.y), "=f"(v.z), "=f"(v.w) : "r"(a) : "memory");
    return v;
}
__device__ __forceinline__ uint32_t add_bf2(uint32_t a, uint32_t b) {
    uint32_t d;
    asm("add.rn.bf16x2 %0, %1, %2;" : "=r"(d) : "r"(a), "r"(b));
    return d;
}
__device__ __forceinline__ uint32_t neg_sq_relu_bf2(uint32_t a) {
    uint32_t d;
    asm("{\n.reg .b32 r, n;\nmax.bf16x2 r, %1, %2;\nneg.bf16x2 n, r;\nmul.rn.bf16x2 %0, r, n;\n}" : "=r"(d) : "r"(a), "r"(0));
    return d;
}

#define V4(v) "+r"(v.x), "+r"(v.y), "+r"(v.z), "+r"(v.w)
#define POLL_HEAD(label) "mov.u32 it, 0;\n" label ":\nadd.u32 it, it, 1;\nsetp.lt.u32 c, it, 4194304;\n"
#define POLL_EXIT(label) "and.pred q, q, c;\nvote.sync.any.pred q, q, 0xffffffff;\n@!q bra " label "_END;\n"
#define POLL_LD(p, regs, addr) "@" p " ld.relaxed.gpu.global.v4.u32 {" regs "}, [" addr "];\n"
__device__ __forceinline__ void poll_nz(uint4& v, const uint32_t* p) {
    asm volatile("{\n.reg .pred p0, q, c;\n.reg .b32 t, it;\n" POLL_HEAD("PA")
                 "min.u32 t, %0, %1;\nmin.u32 t, t, %2;\nmin.u32 t, t, %3;\nsetp.eq.u32 p0, t, 0;\nmov.pred q, p0;\n"
                 POLL_EXIT("PA") POLL_LD("p0", "%0,%1,%2,%3", "%4") "bra PA;\nPA_END:\n}"
                 : V4(v) : "l"(p) : "memory");
}
__device__ __forceinline__ void poll_nz2(uint4& v, uint4& w, const uint32_t* p) {
    asm volatile("{\n.reg .pred p0, p1, q, c;\n.reg .b32 t, u, it;\n" POLL_HEAD("PB")
                 "min.u32 t, %0, %1;\nmin.u32 t, t, %2;\nmin.u32 t, t, %3;\nsetp.eq.u32 p0, t, 0;\n"
                 "min.u32 u, %4, %5;\nmin.u32 u, u, %6;\nmin.u32 u, u, %7;\nsetp.eq.u32 p1, u, 0;\nor.pred q, p0, p1;\n"
                 POLL_EXIT("PB") POLL_LD("p0", "%0,%1,%2,%3", "%8") POLL_LD("p1", "%4,%5,%6,%7", "%8+512") "bra PB;\nPB_END:\n}"
                 : V4(v), V4(w) : "l"(p) : "memory");
}
__device__ __forceinline__ void poll_nz_pair(uint32_t& v, uint32_t& w, const uint32_t* p) {
    asm volatile("{\n.reg .pred q, c;\n.reg .b32 t, it;\n" POLL_HEAD("PC")
                 "ld.relaxed.gpu.global.u32 %0, [%2];\nld.relaxed.gpu.global.u32 %1, [%2+64];\n"
                 "min.u32 t, %0, %1;\nsetp.eq.u32 q, t, 0;\n"
                 POLL_EXIT("PC") "bra PC;\nPC_END:\n}"
                 : "=&r"(v), "=&r"(w) : "l"(p) : "memory");
}
__device__ __forceinline__ void poll_nz4(uint4& a, uint4& b, uint4& c, uint4& d, const uint32_t* p) {
    asm volatile("{\n.reg .pred p0, p1, p2, p3, q, c;\n.reg .b32 t, it;\n" POLL_HEAD("PD")
                 "min.u32 t, %0, %1;\nmin.u32 t, t, %2;\nmin.u32 t, t, %3;\nsetp.eq.u32 p0, t, 0;\n"
                 "min.u32 t, %4, %5;\nmin.u32 t, t, %6;\nmin.u32 t, t, %7;\nsetp.eq.u32 p1, t, 0;\n"
                 "min.u32 t, %8, %9;\nmin.u32 t, t, %10;\nmin.u32 t, t, %11;\nsetp.eq.u32 p2, t, 0;\n"
                 "min.u32 t, %12, %13;\nmin.u32 t, t, %14;\nmin.u32 t, t, %15;\nsetp.eq.u32 p3, t, 0;\n"
                 "or.pred q, p0, p1;\nor.pred q, q, p2;\nor.pred q, q, p3;\n"
                 POLL_EXIT("PD") POLL_LD("p0", "%0,%1,%2,%3", "%16") POLL_LD("p1", "%4,%5,%6,%7", "%16+512")
                 POLL_LD("p2", "%8,%9,%10,%11", "%16+1024") POLL_LD("p3", "%12,%13,%14,%15", "%16+1536") "bra PD;\nPD_END:\n}"
                 : V4(a), V4(b), V4(c), V4(d) : "l"(p) : "memory");
}
__device__ __forceinline__ void poll_sign4(uint4& a, uint4& b, uint4& c, uint4& d, const uint32_t* p) {
    asm volatile("{\n.reg .pred p0, p1, p2, p3, q, c;\n.reg .b32 t, it;\n" POLL_HEAD("PE")
                 "lop3.b32 t, %0, %1, %2, 0x80;\nlop3.b32 t, t, %3, 0x80000000, 0x2a;\nsetp.ne.u32 p0, t, 0;\n"
                 "lop3.b32 t, %4, %5, %6, 0x80;\nlop3.b32 t, t, %7, 0x80000000, 0x2a;\nsetp.ne.u32 p1, t, 0;\n"
                 "lop3.b32 t, %8, %9, %10, 0x80;\nlop3.b32 t, t, %11, 0x80000000, 0x2a;\nsetp.ne.u32 p2, t, 0;\n"
                 "lop3.b32 t, %12, %13, %14, 0x80;\nlop3.b32 t, t, %15, 0x80000000, 0x2a;\nsetp.ne.u32 p3, t, 0;\n"
                 "or.pred q, p0, p1;\nor.pred q, q, p2;\nor.pred q, q, p3;\n"
                 POLL_EXIT("PE") POLL_LD("p0", "%0,%1,%2,%3", "%16") POLL_LD("p1", "%4,%5,%6,%7", "%16+256")
                 POLL_LD("p2", "%8,%9,%10,%11", "%16+512") POLL_LD("p3", "%12,%13,%14,%15", "%16+768") "bra PE;\nPE_END:\n}"
                 : V4(a), V4(b), V4(c), V4(d) : "l"(p) : "memory");
}

constexpr uint32_t ONES = 0x3f803f80u;

__device__ __forceinline__ void ffn1_finish(uint32_t bar, uint32_t a_w1, uint32_t a_part, uint32_t a_stat,
                                            uint32_t bias_a, uint32_t bias_b, uint32_t* dst) {
    float w0[4] = {}, w1[4] = {}, w2[4] = {}, w3[4] = {};
    mbar_wait(bar, 0);
#pragma unroll 1
    for (int s = 0; s < 28; s += 14) {
        uint4 bw[14];
#pragma unroll
        for (int i = 0; i < 14; i++) bw[i] = ldm4t(a_w1 + (s + i) * 1024);
#pragma unroll
        for (int i = 0; i < 14; i += 2) {
            mma16816(w0, ONES, ONES, ONES, ONES, bw[i].x, bw[i].y);
            mma16816(w1, ONES, ONES, ONES, ONES, bw[i].z, bw[i].w);
            mma16816(w2, ONES, ONES, ONES, ONES, bw[i + 1].x, bw[i + 1].y);
            mma16816(w3, ONES, ONES, ONES, ONES, bw[i + 1].z, bw[i + 1].w);
        }
    }
    const float cs0 = w0[0] + w2[0], cs1 = w0[1] + w2[1], cs2 = w1[0] + w3[0], cs3 = w1[1] + w3[1];
    asm volatile("barrier.sync 2, 288;" ::: "memory");
    float2 sq[7];
    float4 p[7];
#pragma unroll
    for (int w = 0; w < 7; w++) sq[w] = lds64f(a_stat + w * 64);
#pragma unroll
    for (int w = 0; w < 7; w++) p[w] = lds128f(a_part + w * 1024);
    const float sum = ((sq[0].x + sq[1].x) + (sq[2].x + sq[3].x)) + ((sq[4].x + sq[5].x) + sq[6].x);
    const float mean = sum * (1.0f / DM);
    const float msq = (((sq[0].y + sq[1].y) + (sq[2].y + sq[3].y)) + ((sq[4].y + sq[5].y) + sq[6].y)) * (1.0f / DM);
    const float var = fmaxf(fmaf(-mean, mean, msq), 0.f);
    float sd, rs;
    asm("sqrt.approx.ftz.f32 %0, %1;" : "=f"(sd) : "f"(rbf(rbf(var) + 1e-5f)));
    asm("rcp.approx.ftz.f32 %0, %1;" : "=f"(rs) : "f"(rbf(sd)));
    const float mb = rbf(fmaf(fmaf(-mean, (float)DM, sum), 1.0f / DM, mean));
    const float s0 = fmaf(-mb, cs0, ((p[0].x + p[1].x) + (p[2].x + p[3].x)) + ((p[4].x + p[5].x) + p[6].x));
    const float s1 = fmaf(-mb, cs1, ((p[0].y + p[1].y) + (p[2].y + p[3].y)) + ((p[4].y + p[5].y) + p[6].y));
    const float s2 = fmaf(-mb, cs2, ((p[0].z + p[1].z) + (p[2].z + p[3].z)) + ((p[4].z + p[5].z) + p[6].z));
    const float s3 = fmaf(-mb, cs3, ((p[0].w + p[1].w) + (p[2].w + p[3].w)) + ((p[4].w + p[5].w) + p[6].w));
    st_rlx64(dst, neg_sq_relu_bf2(add_bf2(pack_bf(s0 * rs, s1 * rs), bias_a)),
             neg_sq_relu_bf2(add_bf2(pack_bf(s2 * rs, s3 * rs), bias_b)));
}

__global__ void __launch_bounds__(NTHREADS, 1)
fused_decode_kernel(Scratch* gs, const char* __restrict__ kc,
                    const __nv_bfloat16* __restrict__ x, const __nv_bfloat16* __restrict__ wq,
                    const __nv_bfloat16* __restrict__ b1, const __nv_bfloat16* __restrict__ b2,
                    __nv_bfloat16* __restrict__ out,
                    const __grid_constant__ CUtensorMap tm_k, const __grid_constant__ CUtensorMap tm_v,
                    const __grid_constant__ CUtensorMap tm_wo, const __grid_constant__ CUtensorMap tm_w1,
                    const __grid_constant__ CUtensorMap tm_w2) {
    if (threadIdx.x == 256)
        asm volatile("cp.async.bulk.prefetch.L2.global [%0], %1;"
                     :: "l"(kc + ((size_t)(((blockIdx.x & 7) * NH + (blockIdx.x >> 3)) * 2 + ((blockIdx.x >> 3) & 1)) << 20)),
                        "r"(STAGE) : "memory");
    extern __shared__ __align__(1024) uint8_t sp[];
    const uint32_t sb = pin(smem_u32(sp));

    const int tid = threadIdx.x, warp = tid >> 5, lane = tid & 31;
    const int g = lane >> 2, t4 = lane & 3;
    const int cta = blockIdx.x;
    const int hd = cta >> 3, bj = cta & 7;
    const bool tail = bj < 7;
    const int ri = (hd * 7 + bj) >> 1;
    const bool ffn2 = (hd + bj) & 1;
    const int bg = ri & 1, cg = ri >> 1;
    const uint32_t bar_full = sb + OFF_BAR, bar_empty = bar_full + NS * 8, bar_w = bar_empty + NS * 8;
    const uint32_t s_wq = sb + OFF_WO, s_est = sb + OFF_M + 64;

    uint32_t epoch;
    asm volatile("ld.relaxed.gpu.global.u32 %0, [%1];" : "=r"(epoch) : "l"(gs->epoch[cta]) : "memory");
    const int grp0 = (bj * NH + hd) * (SK / 8), flip = (hd & 1) * (KT / 2);
    uint64_t pol;
    asm volatile("createpolicy.fractional.L2::evict_first.b64 %0, 1.0;" : "=l"(pol));
    if (tid == 256) {
#pragma unroll
        for (int s = 0; s < D0; s++) mbar_init(bar_full + s * 8, 1);
        asm volatile("fence.mbarrier_init.release.cluster;" ::: "memory");
#pragma unroll
        for (int s = 0; s < D0; s++) {
            mbar_expect_tx(bar_full + s * 8, STAGE);
            tma_tile(sb + OFF_RING + s * STAGE, &tm_k, grp0 + (s ^ flip) * 4, bar_full + s * 8, pol);
        }
    }
    uint4 xr0 = make_uint4(0, 0, 0, 0), xr1 = xr0;
    if (warp < 8) {
        if (lane < 28) {
            xr0 = ldg128_now(x + warp * DM + lane * 8);
            xr1 = ldg128_now(x + warp * DM + 224 + lane * 8);
        }
        const int row = tid >> 2, ch = tid & 3;
        const uint32_t d = s_wq + row * 64 + ((ch ^ ((row >> 1) & 3)) << 4);
        const __nv_bfloat16* p = wq + (size_t)row * (NH * DH) + cta * 32 + ch * 8;
#pragma unroll
        for (int i = 0; i < 7; i++)
            asm volatile("cp.async.cg.shared.global.L2::128B [%0], [%1], 16;"
                         :: "r"(d + i * 4096), "l"(p + (size_t)i * 64 * (NH * DH)) : "memory");
    }

    if (warp == 8) {
        if (lane != 0) return;
#pragma unroll
        for (int s = D0; s < 2 * NS + 9; s++) mbar_init(bar_full + s * 8, (s >= NS && s < 2 * NS) || s == 2 * NS + 1 ? 8 : 1);
        asm volatile("fence.mbarrier_init.release.cluster;" ::: "memory");
        asm volatile("st.volatile.shared.v2.u32 [%0], {%1,%2};" :: "r"(s_est), "r"(0), "r"(clock32()) : "memory");
        asm volatile("barrier.arrive 3, 288;" ::: "memory");
        asm volatile("barrier.arrive 7, 64;" ::: "memory");
        uint32_t t = D0, landed = 0, pf = NS;
#pragma unroll 1
        for (int it = 0; t < NT && it < 16 * SPIN_MAX; it++) {
            if (landed < t && mbar_test(bar_full + (landed & (NS - 1)) * 8, (landed / NS) & 1)) {
                landed++;
                if (((landed + cta) & 3) == 0) asm volatile("red.relaxed.gpu.global.add.u32 [%0], 4;" :: "l"(gs->prog[~pin(epoch) & 1]) : "memory");
            }
            const uint32_t s = t & (NS - 1);
            if (t < NS) {
                if (t - landed >= D0) continue;
            } else {
                if (t == NS && pf - landed < D0 && !mbar_test(bar_empty, 0)) {
                    asm volatile("cp.async.bulk.prefetch.tensor.4d.L2.global [%0, {%1, %1, %1, %2}];"
                                 :: "l"(&tm_k), "r"(0), "r"(grp0 + (pf ^ flip) * 4) : "memory");
                    pf++;
                }
                if (t - landed >= NS) continue;
                if (t - landed >= 2) {
                    uint32_t v, c0;
                    asm volatile("ld.volatile.shared.v2.u32 {%0,%1}, [%2];" : "=r"(v), "=r"(c0) : "r"(s_est) : "memory");
                    if (t * NCTA > v + min(((clock32() - c0) * 7) >> 6, 256u) + (t - landed > 2 ? WIN : WIN + EXTRA)) continue;
                }
                if (!mbar_test(bar_empty + s * 8, (t / NS - 1) & 1)) continue;
            }
            mbar_expect_tx(bar_full + s * 8, STAGE);
            tma_tile(sb + OFF_RING + s * STAGE, t < KT ? &tm_k : &tm_v, grp0 + ((t ^ flip) & (KT - 1)) * 4, bar_full + s * 8, pol);
            t++;
        }
        asm volatile("red.relaxed.gpu.global.add.u32 [%0], %1;" :: "l"(gs->prog[~epoch & 1]), "r"(NT - ((landed + (cta & 3)) & ~3u)) : "memory");
        if (!tail) return;
        mbar_wait(bar_full + ((NT - 1 - XO) & (NS - 1)) * 8, ((NT - 1 - XO) / NS) & 1);
        mbar_expect_tx(bar_w, DH * 128);
        tma_2d(sb + OFF_WO, &tm_wo, bj * 64, hd * DH, bar_w);
        if (!ffn2) {
            mbar_wait(bar_w, 0);
            mbar_expect_tx(bar_w + 16, DM * 64);
            tma_2d(sb + OFF_W, &tm_w1, ri * 32, 0, bar_w + 16);
            tma_2d(sb + OFF_W + 224 * 64, &tm_w1, ri * 32, 224, bar_w + 16);
        } else {
            mbar_wait(bar_w + 8, 0);
#pragma unroll
            for (int i = 0; i < 7; i++) {
                mbar_expect_tx(bar_w + (2 + i) * 8, 8192);
                tma_2d(sb + OFF_RING + i * 8192, &tm_w2, cg * 16, i * 256, bar_w + (2 + i) * 8);
            }
        }
        return;
    }

    const uint32_t par = (epoch + 1) & 1;
    if (warp == 10) {
        __nanosleep(CLEAR_NS);
        const uint4 z = make_uint4(0, 0, 0, 0);
        for (int i = lane; i < MAIL_VECS; i += 32) reinterpret_cast<uint4*>(&gs->mail)[cta * MAIL_VECS + i] = z;
        reinterpret_cast<uint4*>(gs->q[par ^ 1])[cta * 32 + lane] = z;
        if (cta == 0 && lane == 0) { gs->prog[par ^ 1][0] = 0; gs->cleared[par ^ 1][0] = 0; }
        __syncwarp();
        if (lane == 0) {
            asm volatile("red.release.gpu.global.add.u32 [%0], 1;" :: "l"(gs->cleared[par]) : "memory");
            uint32_t n = 0;
#pragma unroll 1
            for (int it = 0; n < NCTA && it < SPIN_MAX; it++) {
                __nanosleep(1000);
                asm volatile("ld.acquire.gpu.global.u32 %0, [%1];" : "=r"(n) : "l"(gs->cleared[par]) : "memory");
            }
        }
        __syncwarp();
        asm volatile("barrier.arrive 8, 288;" ::: "memory");
        return;
    }
    const uint32_t a_w1 = pin(sb + OFF_W + (((lane >> 3) & 1) * 8 + (lane & 7)) * 64 + (((lane >> 4) ^ ((lane >> 1) & 3)) << 4));
    const uint32_t a_stat = pin(sb + OFF_D + 7168 + g * 8);

    if (warp == 9) {
        uint32_t bias_a = 0, bias_b = 0;
        if (tail && !ffn2) {
            bias_a = ldg32_now(b1 + ri * 32 + 16 + t4 * 2);
            bias_b = ldg32_now(b1 + ri * 32 + 24 + t4 * 2);
        }
        uint4 q = make_uint4(0, 0, 0, 0);
        poll_nz(q, &gs->q[par][bj * (NH * DH / 2) + hd * (DH / 2) + lane * 4]);
        *reinterpret_cast<uint4*>(sp + OFF_Q + lane * 16) = q;
        asm volatile("barrier.arrive 5, 288;" ::: "memory");
        asm volatile("barrier.sync 7, 64;" ::: "memory");
        if (lane == 0) {
            asm volatile("prefetch.tensormap [%0];" :: "l"(&tm_v) : "memory");
            asm volatile("prefetch.tensormap [%0];" :: "l"(&tm_wo) : "memory");
            asm volatile("prefetch.tensormap [%0];" :: "l"(ffn2 ? &tm_w2 : &tm_w1) : "memory");
            uint32_t v = 0;
#pragma unroll 1
            for (int it = 0; v + WIN < (NT - 1) * NCTA && it < SPIN_MAX; it++) {
                asm volatile("ld.relaxed.gpu.global.u32 %0, [%1];" : "=r"(v) : "l"(gs->prog[par]) : "memory");
                asm volatile("st.volatile.shared.v2.u32 [%0], {%1,%2};" :: "r"(s_est), "r"(v), "r"(clock32()) : "memory");
                __nanosleep(HSLEEP);
            }
        }
        __syncwarp();
        if (tail && !ffn2) {
            ffn1_finish(bar_w + 16, a_w1 ^ 32, pin(sb + OFF_D + 512 + lane * 16), a_stat, bias_a, bias_b,
                        pin(&gs->mail.g[((g >> 2) * NMSG + ri * 2 + 1) * 32 + (g & 3) * 8 + (t4 ^ 1) * 2]));
        }
        return;
    }

    asm volatile("cp.async.commit_group;" ::: "memory");
    uint32_t c0w = 0, c1w = 0;
    if (!tail) {
        if (warp < 7) {
            const __nv_bfloat16* p = x + (hd >> 1) * DM + warp * 64 + (hd & 1) * 32 + ((lane >> 2) & 1) * 16 + t4 * 2;
            c0w = ldg32_now(p);
            c1w = ldg32_now(p + 8);
        }
    } else if (warp == 7) {
        if (ffn2) {
            c0w = ldg32_now(b2 + cg * 16 + (lane & 1) * 8 + (g & 6));
            c0w = __byte_perm(c0w, 0, (g & 1) ? 0x3232 : 0x1010);
        } else {
            c0w = ldg32_now(b1 + ri * 32 + t4 * 2);
            c1w = ldg32_now(b1 + ri * 32 + 8 + t4 * 2);
        }
    }

    layernorm_row(xr0, xr1, lane, sb + OFF_C + warp * (XP * 2));
    asm volatile("cp.async.wait_group 0;" ::: "memory");
    asm volatile("barrier.sync 3, 288;" ::: "memory");

    float* red_b = reinterpret_cast<float*>(sp + OFF_B);
    if (warp < 7) {
        float acc[4][4] = {};
#pragma unroll
        for (int p = 0; p < 2; p++) {
            const uint4 a = ldm4(sb + OFF_C + (lane & 7) * (XP * 2) + (warp * 64 + p * 32 + (lane >> 3) * 8) * 2);
#pragma unroll
            for (int s = 0; s < 2; s++) {
                const int row = warp * 64 + p * 32 + s * 16 + ((lane >> 3) & 1) * 8 + (lane & 7);
#pragma unroll
                for (int np = 0; np < 2; np++) {
                    const int ch = np * 2 + (lane >> 4);
                    const uint4 bw = ldm4t(s_wq + row * 64 + ((ch ^ ((row >> 1) & 3)) << 4));
                    mma16816(acc[np * 2], s ? a.z : a.x, 0, s ? a.w : a.y, 0, bw.x, bw.y);
                    mma16816(acc[np * 2 + 1], s ? a.z : a.x, 0, s ? a.w : a.y, 0, bw.z, bw.w);
                }
            }
        }
#pragma unroll
        for (int n = 0; n < 4; n++)
            *reinterpret_cast<float2*>(red_b + (warp * 8 + g) * 40 + n * 8 + t4 * 2) = make_float2(acc[n][0], acc[n][1]);
    }
    asm volatile("fence.proxy.async.shared::cta;" ::: "memory");
    cbar();
    if (tid < 128) {
        const int b = tid >> 4, wd = tid & 15;
        float s0 = 0.f, s1 = 0.f;
#pragma unroll
        for (int w = 0; w < 7; w++) {
            const float2 p = *reinterpret_cast<const float2*>(red_b + (w * 8 + b) * 40 + wd * 2);
            s0 += p.x; s1 += p.y;
        }
        st_rlx32(&gs->q[par][b * (NH * DH / 2) + cta * 16 + (wd & 3) * 4 + ((wd >> 2) & 1) * 2 + (wd >> 3)], enc(pack_bf(s0, s1)));
    }

    uint32_t* const p_o_st = pin(&gs->mail.o[(hd * 8 + warp) * 128 + bj * 16 + t4 * 4]);
    const uint32_t* const p_o_ld = pin(&gs->mail.o[(hd * 8 + warp) * 128 + lane * 4]);
    uint32_t* const p_p2_st = pin(gs->mail.p2 + ((bj * 16 + warp * 2 + (lane >> 4)) * 16 + hd) * 32 + (lane & 15) * 2);
    const uint32_t* p_in;
    uint32_t* p_res;
    if (!tail) {
        p_in = gs->mail.p2 + ((warp * 16 + hd) * 16 + (lane >> 3)) * 32 + (lane & 7) * 4;
        p_res = &gs->mail.h[(lane >> 3) % HREP][(warp * 2 + (hd & 1)) * 128 + (hd >> 1) * 16 + t4 * 4 + ((lane >> 2) & 1) * 2];
    } else if (!ffn2) {
        p_in = &gs->mail.h[ri % HREP][warp * 256 + lane * 4];
        p_res = &gs->mail.g[((g >> 2) * NMSG + ri * 2) * 32 + (g & 3) * 8 + t4 * 2];
    } else {
        const int b = bg * 4 + (lane & 2);
        p_in = warp < 7 ? &gs->mail.g[(bg * NMSG + warp * 16 + (g >> 2) * 8 + (t4 >> 1)) * 32 + (g & 3) * 8 + (t4 & 1) * 4]
                        : &gs->mail.h[ri % HREP][(cg >> 1) * 128 + b * 16 + (g >> 1) * 4 + (cg & 1) * 2 + (lane & 1)];
        p_res = reinterpret_cast<uint32_t*>(out + b * DM + cg * 16 + (lane & 1) * 8 + g);
    }
    p_in = pin(p_in);
    p_res = pin(p_res);
    const uint32_t a_wo = pin(sb + OFF_WO + (warp * 32 + (lane >> 4) * 8 + (lane & 7)) * 128 + ((((lane >> 3) & 1) ^ (lane & 7)) << 4));
    const uint32_t a_r2w = pin(sb + OFF_B + warp * 2048 + (t4 * 8 + ((g + 2 * t4) & 7)) * 16);
    const uint32_t a_r2r = pin(sb + OFF_B + (lane >> 3) * 512 +
                               ((warp >> 1) * 8 + ((lane + (warp & 6)) & 7)) * 16 + ((warp ^ (lane >> 3)) & 1) * 8);
    __nv_bfloat16* sc = reinterpret_cast<__nv_bfloat16*>(sp + OFF_A);

    float mx = -INFINITY;
    {
        uint4 q[8];
        asm volatile("barrier.sync 5, 288;" ::: "memory");
#pragma unroll
        for (int i = 0; i < 8; i++) q[i] = lds128(sb + OFF_Q + i * 64 + t4 * 16);
        const uint32_t ka = pin(sb + OFF_RING + (warp & 3) * 4096 + (lane & 7) * 128 + (((lane >> 3) ^ (lane & 7)) << 4));
        uint32_t* scw = reinterpret_cast<uint32_t*>(sc) + t4 * 4 + (warp & 1) * 2 + ((warp >> 1) & 1);
#pragma unroll 1
        for (int t = warp >> 2; t < KT; t += 2) {
            const int st = t & (NS - 1);
            mbar_wait(bar_full + st * 8, (t / NS) & 1);
            uint4 kf[8];
#pragma unroll
            for (int i = 0; i < 8; i++) kf[i] = ldm4((ka ^ ((i & 1) << 6)) + st * STAGE + (i >> 1) * 1024);
            float c[4][4] = {};
#pragma unroll
            for (int i = 0; i < 8; i++) {
                mma16816(c[(i & 1) * 2], q[i].x, q[i].y, q[i].z, q[i].w, kf[i].x, kf[i].y);
                mma16816(c[(i & 1) * 2 + 1], q[i].x, q[i].y, q[i].z, q[i].w, kf[i].z, kf[i].w);
            }
            __syncwarp();
            if (lane == 0) mbar_arrive2(bar_empty + st * 8);
            const uint32_t d = pack_bf((c[0][0] + c[2][0]) + (c[1][2] + c[3][2]), (c[0][1] + c[2][1]) + (c[1][3] + c[3][3]));
            const uint32_t sw = pack_bf(bf_lo(d) * 0.0625f, bf_hi(d) * 0.0625f);
            mx = fmaxf(mx, fmaxf(bf_lo(sw), bf_hi(sw)));
            if (lane < 4) scw[t * 16] = sw;
        }
    }

    {
        float* sm_m = reinterpret_cast<float*>(sp + OFF_M);
        mx = fmaxf(mx, __shfl_xor_sync(0xffffffffu, mx, 1));
        mx = fmaxf(mx, __shfl_xor_sync(0xffffffffu, mx, 2));
        if (lane == 0) sm_m[warp] = mx;
        cbar();
#pragma unroll
        for (int w = 0; w < 8; w++) mx = fmaxf(mx, sm_m[w]);
        float e[16], sum = 0.f;
#pragma unroll
        for (int i = 0; i < 4; i++) {
            const uint2 s = *reinterpret_cast<const uint2*>(sc + i * 1024 + tid * 4);
            e[i * 4 + 0] = expf(bf_lo(s.x) - mx); e[i * 4 + 1] = expf(bf_hi(s.x) - mx);
            e[i * 4 + 2] = expf(bf_lo(s.y) - mx); e[i * 4 + 3] = expf(bf_hi(s.y) - mx);
            sum += (e[i * 4] + e[i * 4 + 1]) + (e[i * 4 + 2] + e[i * 4 + 3]);
        }
        sum = warp_sum(sum);
        if (lane == 0) sm_m[8 + warp] = sum;
        cbar();
        sum = 0.f;
#pragma unroll
        for (int w = 0; w < 8; w++) sum += sm_m[8 + w];
        const float inv = 1.0f / sum;
#pragma unroll
        for (int i = 0; i < 4; i++)
            *reinterpret_cast<uint2*>(sc + i * 1024 + tid * 4) =
                make_uint2(pack_bf(e[i * 4] * inv, e[i * 4 + 1] * inv), pack_bf(e[i * 4 + 2] * inv, e[i * 4 + 3] * inv));
        asm volatile("barrier.sync 8, 288;" ::: "memory");
    }
    if (tid == 0) st_rlx32(gs->epoch[cta], epoch + 1);

    uint4 ov = make_uint4(0, 0, 0, 0);
    {
        float oa[4][4] = {}, ob[4][4] = {};
        const uint32_t va = pin(sb + OFF_RING + ((lane >> 3) & 1) * 4096 + (warp >> 1) * 1024 + (lane & 7) * 128 +
                                ((((warp & 1) * 4 + (lane >> 4)) ^ (lane & 7)) << 4));
        auto pv_tile = [&](int t) {
            const int st = t & (NS - 1);
            const uint4 p = lds128(sb + OFF_A + t * 64 + t4 * 16);
            const uint32_t va0 = pin(va + st * STAGE), va1 = pin(va0 ^ 32);
            mbar_wait(bar_full + st * 8, ((KT + t) / NS) & 1);
            const uint4 v0 = ldm4t(va0), v1 = ldm4t(va1), v2 = ldm4t(va0 + 8192), v3 = ldm4t(va1 + 8192);
            mma16816(oa[0], p.x, p.y, p.z, p.w, v0.x, v0.y);
            mma16816(oa[1], p.x, p.y, p.z, p.w, v0.z, v0.w);
            mma16816(oa[2], p.x, p.y, p.z, p.w, v1.x, v1.y);
            mma16816(oa[3], p.x, p.y, p.z, p.w, v1.z, v1.w);
            mma16816(ob[0], p.x, p.y, p.z, p.w, v2.x, v2.y);
            mma16816(ob[1], p.x, p.y, p.z, p.w, v2.z, v2.w);
            mma16816(ob[2], p.x, p.y, p.z, p.w, v3.x, v3.y);
            mma16816(ob[3], p.x, p.y, p.z, p.w, v3.z, v3.w);
            __syncwarp();
            if (lane == 0) mbar_arrive(bar_empty + st * 8);
        };
#pragma unroll 1
        for (int t = 0; t < KT - OEARLY; t++) pv_tile(t);
        ld_rlx128_if(tail, ov, p_o_ld);
#pragma unroll 1
        for (int t = KT - OEARLY; t < KT; t++) pv_tile(t);
        st_rlx128_if(lane < 4, p_o_st,
                     enc(pack_bf(oa[0][0] + ob[0][2], oa[0][1] + ob[0][3])), enc(pack_bf(oa[1][0] + ob[1][2], oa[1][1] + ob[1][3])),
                     enc(pack_bf(oa[2][0] + ob[2][2], oa[2][1] + ob[2][3])), enc(pack_bf(oa[3][0] + ob[3][2], oa[3][1] + ob[3][3])));
    }

    if (!tail) {
        if (warp < 7) {
            uint4 v0 = make_uint4(0, 0, 0, 0), v1 = v0, v2 = v0, v3 = v0;
            poll_nz4(v0, v1, v2, v3, p_in);
            float a0 = (__uint_as_float(v0.x) + __uint_as_float(v1.x)) + (__uint_as_float(v2.x) + __uint_as_float(v3.x));
            float a1 = (__uint_as_float(v0.y) + __uint_as_float(v1.y)) + (__uint_as_float(v2.y) + __uint_as_float(v3.y));
            float a2 = (__uint_as_float(v0.z) + __uint_as_float(v1.z)) + (__uint_as_float(v2.z) + __uint_as_float(v3.z));
            float a3 = (__uint_as_float(v0.w) + __uint_as_float(v1.w)) + (__uint_as_float(v2.w) + __uint_as_float(v3.w));
#pragma unroll
            for (int o = 8; o <= 16; o <<= 1) {
                a0 += __shfl_xor_sync(0xffffffffu, a0, o);
                a1 += __shfl_xor_sync(0xffffffffu, a1, o);
                a2 += __shfl_xor_sync(0xffffffffu, a2, o);
                a3 += __shfl_xor_sync(0xffffffffu, a3, o);
            }
            st_rlx64_if(lane < 8 * HREP, p_res, enc(add_bf2(c0w, pack_bf(a0, a2))), enc(add_bf2(c1w, pack_bf(a1, a3))));
        }
        return;
    }

    {
        uint4 v = ov;
        mbar_wait(bar_w, 0);
        ld_rlx128_if(min(min(v.x, v.y), min(v.z, v.w)) == 0, v, p_o_ld);
        uint4 a[2][4];
#pragma unroll
        for (int s = 0; s < 2; s++)
#pragma unroll
            for (int mt = 0; mt < 4; mt++) a[s][mt] = ldm4t((a_wo ^ (mt << 5)) + s * 2048);
        poll_nz(v, p_o_ld);
        float acc[4][4] = {};
#pragma unroll
        for (int mt = 0; mt < 4; mt++) mma16816(acc[mt], a[0][mt].x, a[0][mt].y, a[0][mt].z, a[0][mt].w, v.x, v.y);
#pragma unroll
        for (int mt = 0; mt < 4; mt++) mma16816(acc[mt], a[1][mt].x, a[1][mt].y, a[1][mt].z, a[1][mt].w, v.z, v.w);
#pragma unroll
        for (int mt = 0; mt < 4; mt += 2) {
            sts128(a_r2w + mt * 512, acc[mt][0], acc[mt][2], acc[mt][1], acc[mt][3]);
            sts128(a_r2w + mt * 512 + 512, acc[mt + 1][1], acc[mt + 1][3], acc[mt + 1][0], acc[mt + 1][2]);
        }
        cbar();
        float2 p[8];
#pragma unroll
        for (int w = 0; w < 8; w++) p[w] = lds64f(a_r2r + w * 2048);
        const float s0 = ((p[0].x + p[1].x) + (p[2].x + p[3].x)) + ((p[4].x + p[5].x) + (p[6].x + p[7].x));
        const float s1 = ((p[0].y + p[1].y) + (p[2].y + p[3].y)) + ((p[4].y + p[5].y) + (p[6].y + p[7].y));
        st_rlx64(p_p2_st, enc(__float_as_uint(s0)), enc(__float_as_uint(s1)));
        if (lane == 0) asm volatile("mbarrier.arrive.relaxed.cta.shared.b64 _, [%0];" :: "r"(bar_w + 8) : "memory");
    }

    if (!ffn2) {
        if (warp < 7) {
            uint4 v0 = ld_rlx128(p_in), v1 = ld_rlx128(p_in + 128);
            const uint32_t a_part = pin(sb + OFF_D + warp * 1024 + lane * 16);
            mbar_wait(bar_w + 16, 0);
            uint4 bw[4][2];
#pragma unroll
            for (int s = 0; s < 4; s++) {
                bw[s][0] = ldm4t(a_w1 + warp * 4096 + s * 1024);
                bw[s][1] = ldm4t((a_w1 ^ 32) + warp * 4096 + s * 1024);
            }
            poll_nz2(v0, v1, p_in);
            const uint32_t hw[8] = {v0.x, v0.y, v0.z, v0.w, v1.x, v1.y, v1.z, v1.w};
            float c[4][4] = {}, cs[4] = {};
#pragma unroll
            for (int s = 0; s < 4; s++) {
                mma16816(cs, hw[2 * s], ONES, hw[2 * s + 1], ONES, hw[2 * s], hw[2 * s + 1]);
                mma16816(c[0], hw[2 * s], ONES, hw[2 * s + 1], ONES, bw[s][0].x, bw[s][0].y);
                mma16816(c[1], hw[2 * s], ONES, hw[2 * s + 1], ONES, bw[s][0].z, bw[s][0].w);
                mma16816(c[2], hw[2 * s], ONES, hw[2 * s + 1], ONES, bw[s][1].x, bw[s][1].y);
                mma16816(c[3], hw[2 * s], ONES, hw[2 * s + 1], ONES, bw[s][1].z, bw[s][1].w);
            }
            if (t4 == (g >> 1)) sts64(a_stat + warp * 64, (g & 1) ? cs[3] : cs[2], (g & 1) ? cs[1] : cs[0]);
            sts128(a_part, c[0][0], c[0][1], c[1][0], c[1][1]);
            sts128(a_part + 512, c[2][0], c[2][1], c[3][0], c[3][1]);
            asm volatile("barrier.arrive 2, 288;" ::: "memory");
        } else {
            ffn1_finish(bar_w + 16, a_w1, pin(sb + OFF_D + lane * 16), a_stat, c0w, c1w, p_res);
        }
    } else if (warp < 7) {
        const uint32_t a0 = pin(sb + OFF_RING + warp * 8192 +
                                (((lane >> 2) & 1) * 18 + (lane >> 4) * 8 + ((lane >> 1) & 1) * 4 + (lane & 1)) * 32 +
                                ((((lane >> 3) ^ (lane >> 1)) & 1) << 4));
        const uint32_t a_r5 = pin(sb + OFF_D + warp * 256 + (t4 >> 1) * 1856 + (g * 2 + (t4 & 1)) * 16);
        mbar_wait(bar_w + (2 + warp) * 8, 0);
        uint4 aw[2][8];
#pragma unroll
        for (int hh = 0; hh < 2; hh++)
#pragma unroll
            for (int s = 0; s < 8; s++) aw[hh][s] = ldm4t((a0 ^ ((s & 1) << 6)) + hh * 4096 + (s >> 1) * 1024);
        asm volatile("barrier.sync 6, 256;" ::: "memory");
        uint4 u[4];
#pragma unroll
        for (int i = 0; i < 4; i++) u[i] = ld_rlx128(p_in + i * 64);
        poll_sign4(u[0], u[1], u[2], u[3], p_in);
        float y[2][2][4] = {};
#pragma unroll
        for (int i = 0; i < 4; i++)
#pragma unroll
            for (int hh = 0; hh < 2; hh++) {
                mma16816(y[hh][0], aw[hh][2 * i].x, aw[hh][2 * i].y, aw[hh][2 * i].z, aw[hh][2 * i].w, u[i].x, u[i].y);
                mma16816(y[hh][1], aw[hh][2 * i + 1].x, aw[hh][2 * i + 1].y, aw[hh][2 * i + 1].z, aw[hh][2 * i + 1].w, u[i].z, u[i].w);
            }
        const bool lo = t4 < 2;
        sts128(a_r5, lo ? y[0][0][0] + y[0][1][0] : y[1][0][0] + y[1][1][0], lo ? y[0][0][1] + y[0][1][1] : y[1][0][1] + y[1][1][1],
               lo ? y[0][0][2] + y[0][1][2] : y[1][0][2] + y[1][1][2], lo ? y[0][0][3] + y[0][1][3] : y[1][0][3] + y[1][1][3]);
        asm volatile("barrier.arrive 4, 256;" ::: "memory");
    } else {
        uint32_t h0, h1;
        poll_nz_pair(h0, h1, p_in);
        asm volatile("barrier.arrive 6, 256;" ::: "memory");
        const uint32_t hres = __byte_perm(h0, h1, (g & 1) ? 0x7632 : 0x5410);
        const uint32_t a_r5 = pin(sb + OFF_D + lane * 8);
        asm volatile("barrier.sync 4, 256;" ::: "memory");
        float2 y[14];
#pragma unroll
        for (int w = 0; w < 14; w++) y[w] = lds64f(a_r5 + w * 256 + (w >= 7 ? 64 : 0));
        const float y0 = (((y[0].x + y[1].x) + (y[2].x + y[3].x)) + ((y[4].x + y[5].x) + (y[6].x + y[7].x))) +
                         (((y[8].x + y[9].x) + (y[10].x + y[11].x)) + (y[12].x + y[13].x));
        const float y1 = (((y[0].y + y[1].y) + (y[2].y + y[3].y)) + ((y[4].y + y[5].y) + (y[6].y + y[7].y))) +
                         (((y[8].y + y[9].y) + (y[10].y + y[11].y)) + (y[12].y + y[13].y));
        const uint32_t res = add_bf2(hres, add_bf2(pack_bf(-y0, -y1), c0w));
        asm volatile("st.global.u16 [%0], %1;" :: "l"(p_res), "h"((uint16_t)res) : "memory");
        asm volatile("st.global.u16 [%0+%2], %1;" :: "l"(p_res), "h"((uint16_t)(res >> 16)), "n"(DM * 2) : "memory");
    }
}

typedef CUresult (*EncodeTiledFn)(CUtensorMap*, CUtensorMapDataType, cuuint32_t, void*, const cuuint64_t*,
                                  const cuuint64_t*, const cuuint32_t*, const cuuint32_t*, CUtensorMapInterleave,
                                  CUtensorMapSwizzle, CUtensorMapL2promotion, CUtensorMapFloatOOBfill);

void encode_2d(EncodeTiledFn fn, CUtensorMap* tm, void* base, int rows, int cols, int box_rows, int box_cols,
               CUtensorMapSwizzle sw) {
    cuuint64_t dims[2] = {(cuuint64_t)cols, (cuuint64_t)rows};
    cuuint64_t strides[1] = {(cuuint64_t)cols * 2};
    cuuint32_t box[2] = {(cuuint32_t)box_cols, (cuuint32_t)box_rows};
    cuuint32_t es[2] = {1, 1};
    fn(tm, CU_TENSOR_MAP_DATA_TYPE_BFLOAT16, 2, base, dims, strides, box, es, CU_TENSOR_MAP_INTERLEAVE_NONE, sw,
       CU_TENSOR_MAP_L2_PROMOTION_L2_128B, CU_TENSOR_MAP_FLOAT_OOB_FILL_NONE);
}

void encode_kv(EncodeTiledFn fn, CUtensorMap* tm, void* base) {
    cuuint64_t dims[4] = {64, 8, 4, (cuuint64_t)NB * NH * SK / 8};
    cuuint64_t strides[3] = {DH * 2, 128, 8 * DH * 2};
    cuuint32_t box[4] = {64, 8, 4, TILE_KEYS / 8};
    cuuint32_t es[4] = {1, 1, 1, 1};
    fn(tm, CU_TENSOR_MAP_DATA_TYPE_BFLOAT16, 4, base, dims, strides, box, es, CU_TENSOR_MAP_INTERLEAVE_NONE,
       CU_TENSOR_MAP_SWIZZLE_128B, CU_TENSOR_MAP_L2_PROMOTION_NONE, CU_TENSOR_MAP_FLOAT_OOB_FILL_NONE);
}

}

extern "C" void kernel_launch(void* const* d_in, const int* in_sizes, int n_in, void* d_out, int out_size) {
    (void)in_sizes; (void)n_in; (void)out_size;
    static EncodeTiledFn encode = nullptr;
    static void* scratch = nullptr;
    if (!encode) {
        void* fn = nullptr;
        cudaDriverEntryPointQueryResult qr;
        cudaGetDriverEntryPoint("cuTensorMapEncodeTiled", &fn, cudaEnableDefault, &qr);
        encode = (EncodeTiledFn)fn;
        cudaGetSymbolAddress(&scratch, g_scratch);
        cudaFuncSetAttribute(fused_decode_kernel, cudaFuncAttributeMaxDynamicSharedMemorySize, SMEM_BYTES);
    }
    CUtensorMap tm_k, tm_v, tm_wo, tm_w1, tm_w2;
    encode_kv(encode, &tm_k, d_in[1]);
    encode_kv(encode, &tm_v, d_in[2]);
    encode_2d(encode, &tm_wo, d_in[4], NH * DH, DM, 256, 64, CU_TENSOR_MAP_SWIZZLE_128B);
    encode_2d(encode, &tm_w1, d_in[6], DM, FF, 224, 32, CU_TENSOR_MAP_SWIZZLE_64B);
    encode_2d(encode, &tm_w2, d_in[8], FF, DM, 256, 16, CU_TENSOR_MAP_SWIZZLE_32B);
    fused_decode_kernel<<<NCTA, NTHREADS, SMEM_BYTES, cudaStreamPerThread>>>(
        (Scratch*)scratch, (const char*)d_in[1], (const __nv_bfloat16*)d_in[0], (const __nv_bfloat16*)d_in[3], (const __nv_bfloat16*)d_in[7],
        (const __nv_bfloat16*)d_in[9], (__nv_bfloat16*)d_out, tm_k, tm_v, tm_wo, tm_w1, tm_w2);
}
```

```cpp
#include <cuda_runtime.h>
#include <cuda_bf16.h>
#include <cuda.h>
#include <stdint.h>

namespace {

constexpr int NB = 8, DM = 448, NH = 16, SK = 4096, DH = 256, FF = 1792;
constexpr int NCTA = NB * NH;
constexpr int NMSG = FF / 16;
constexpr int TILE_KEYS = 32;
constexpr int STAGE = TILE_KEYS * DH * 2;
constexpr int NS = 8;
constexpr int KT = SK / TILE_KEYS;
constexpr int NT = 2 * KT;
constexpr int NTHREADS = 352;
constexpr int XP = 456;
constexpr int SPIN_MAX = 1 << 22;

constexpr int D0 = 3;
constexpr int WIN = 416;
constexpr int EXTRA = 192;
constexpr int HSLEEP = 300;
constexpr int WO_DELAY = 400;
constexpr int O_HOLD = 1200;
constexpr int H_HOLD = 1800;
constexpr int HREP = 2;
constexpr int CLEAR_NS = 8000;

constexpr int OFF_RING = 0;
constexpr int OFF_WO = OFF_RING + NS * STAGE;
constexpr int OFF_W = OFF_WO + DH * 128;
constexpr int OFF_A = OFF_W + DM * 64;
constexpr int OFF_B = OFF_A + SK * 2;
constexpr int OFF_Q = OFF_B + 8960;
constexpr int OFF_C = OFF_Q + 512;
constexpr int OFF_D = OFF_C + NB * XP * 2;
constexpr int OFF_M = OFF_D + 7680;
constexpr int OFF_BAR = OFF_M + 128;
constexpr int SMEM_BYTES = OFF_BAR + (2 * NS + 9) * 8;
static_assert(SMEM_BYTES <= 232448, "shared memory budget");
static_assert(OFF_D - OFF_B >= 16384, "the wo reduction reuses the prologue areas");

struct __align__(128) Mail {
    uint32_t o[NH * NB * DH / 2];
    uint32_t p2[7 * 16 * 16 * 32];
    uint32_t h[HREP][NB * DM / 2];
    uint32_t g[2 * NMSG * 32];
};
struct __align__(128) Scratch {
    uint32_t epoch[NCTA][32];
    uint32_t prog[2][32];
    uint32_t cleared[2][32];
    uint32_t q[2][NB * NH * DH / 2];
    Mail mail;
};
__device__ Scratch g_scratch;
constexpr int MAIL_VECS = sizeof(Mail) / 16 / NCTA;
static_assert(sizeof(Mail) % (16 * NCTA) == 0, "equal shares");

__device__ __forceinline__ uint32_t smem_u32(const void* p) { return (uint32_t)__cvta_generic_to_shared(p); }

__device__ __forceinline__ void mbar_init(uint32_t a, uint32_t c) {
    asm volatile("mbarrier.init.shared.b64 [%0], %1;" :: "r"(a), "r"(c) : "memory");
}
__device__ __forceinline__ void mbar_expect_tx(uint32_t a, uint32_t bytes) {
    asm volatile("mbarrier.arrive.expect_tx.shared.b64 _, [%0], %1;" :: "r"(a), "r"(bytes) : "memory");
}
__device__ __forceinline__ void mbar_arrive(uint32_t a) {
    asm volatile("mbarrier.arrive.shared.b64 _, [%0];" :: "r"(a) : "memory");
}
__device__ __forceinline__ void mbar_arrive2(uint32_t a) {
    asm volatile("mbarrier.arrive.shared.b64 _, [%0], 2;" :: "r"(a) : "memory");
}
__device__ __forceinline__ bool mbar_test(uint32_t a, uint32_t parity) {
    uint32_t ok;
    asm volatile("{\n.reg .pred p;\nmbarrier.test_wait.parity.shared.b64 p, [%1], %2;\nselp.u32 %0, 1, 0, p;\n}"
                 : "=r"(ok) : "r"(a), "r"(parity) : "memory");
    return ok;
}
__device__ __forceinline__ uint32_t clock32() {
    uint32_t c;
    asm volatile("mov.u32 %0, %%clock;" : "=r"(c));
    return c;
}
__device__ __forceinline__ void mbar_wait(uint32_t a, uint32_t parity) {
    uint32_t ok;
    int it = 0;
    do {
        asm volatile("{\n.reg .pred p;\nmbarrier.try_wait.parity.shared.b64 p, [%1], %2;\nselp.u32 %0, 1, 0, p;\n}"
                     : "=r"(ok) : "r"(a), "r"(parity) : "memory");
    } while (!ok && ++it < SPIN_MAX);
    if (!ok) __trap();
}
__device__ __forceinline__ void tma_tile(uint32_t dst, const CUtensorMap* tm, int group, uint32_t bar, uint64_t pol) {
    asm volatile("cp.async.bulk.tensor.4d.shared::cluster.global.mbarrier::complete_tx::bytes.L2::cache_hint"
                 " [%0], [%1, {%3, %3, %3, %4}], [%2], %5;"
                 :: "r"(dst), "l"(tm), "r"(bar), "r"(0), "r"(group), "l"(pol) : "memory");
}
__device__ __forceinline__ void tma_2d(uint32_t dst, const CUtensorMap* tm, int c0, int c1, uint32_t bar) {
    asm volatile("cp.async.bulk.tensor.2d.shared::cluster.global.mbarrier::complete_tx::bytes [%0], [%1, {%3, %4}], [%2];"
                 :: "r"(dst), "l"(tm), "r"(bar), "r"(c0), "r"(c1) : "memory");
}
__device__ __forceinline__ void cbar() { asm volatile("barrier.sync 1, 256;" ::: "memory"); }

__device__ __forceinline__ uint4 lds128(uint32_t a) {
    uint4 v;
    asm volatile("ld.shared.v4.u32 {%0,%1,%2,%3}, [%4];" : "=r"(v.x), "=r"(v.y), "=r"(v.z), "=r"(v.w) : "r"(a) : "memory");
    return v;
}
__device__ __forceinline__ uint4 ldm4(uint32_t a) {
    uint4 v;
    asm volatile("ldmatrix.sync.aligned.m8n8.x4.shared.b16 {%0,%1,%2,%3}, [%4];"
                 : "=r"(v.x), "=r"(v.y), "=r"(v.z), "=r"(v.w) : "r"(a) : "memory");
    return v;
}
__device__ __forceinline__ uint4 ldm4t(uint32_t a) {
    uint4 v;
    asm volatile("ldmatrix.sync.aligned.m8n8.x4.trans.shared.b16 {%0,%1,%2,%3}, [%4];"
                 : "=r"(v.x), "=r"(v.y), "=r"(v.z), "=r"(v.w) : "r"(a) : "memory");
    return v;
}
__device__ __forceinline__ void mma16816(float (&c)[4], uint32_t a0, uint32_t a1, uint32_t a2, uint32_t a3, uint32_t b0, uint32_t b1) {
    asm volatile("mma.sync.aligned.m16n8k16.row.col.f32.bf16.bf16.f32 {%0,%1,%2,%3}, {%4,%5,%6,%7}, {%8,%9}, {%0,%1,%2,%3};"
                 : "+f"(c[0]), "+f"(c[1]), "+f"(c[2]), "+f"(c[3])
                 : "r"(a0), "r"(a1), "r"(a2), "r"(a3), "r"(b0), "r"(b1));
}
__device__ __forceinline__ uint4 ld_rlx128(const uint32_t* p) {
    uint4 v;
    asm volatile("ld.relaxed.gpu.global.v4.u32 {%0,%1,%2,%3}, [%4];" : "=r"(v.x), "=r"(v.y), "=r"(v.z), "=r"(v.w) : "l"(p) : "memory");
    return v;
}
__device__ __forceinline__ uint32_t ldg32_now(const void* p) {
    uint32_t v;
    asm volatile("ld.global.nc.u32 %0, [%1];" : "=r"(v) : "l"(p) : "memory");
    return v;
}
__device__ __forceinline__ uint4 ldg128_now(const void* p) {
    uint4 v;
    asm volatile("ld.global.nc.v4.u32 {%0,%1,%2,%3}, [%4];" : "=r"(v.x), "=r"(v.y), "=r"(v.z), "=r"(v.w) : "l"(p) : "memory");
    return v;
}
__device__ __forceinline__ void st_rlx32(uint32_t* p, uint32_t v) {
    asm volatile("st.relaxed.gpu.global.u32 [%0], %1;" :: "l"(p), "r"(v) : "memory");
}
__device__ __forceinline__ void st_rlx64(uint32_t* p, uint32_t a, uint32_t b) {
    asm volatile("st.relaxed.gpu.global.v2.u32 [%0], {%1,%2};" :: "l"(p), "r"(a), "r"(b) : "memory");
}

__device__ __forceinline__ void st_rlx64_if(bool c, uint32_t* p, uint32_t a, uint32_t b) {
    asm volatile("{\n.reg .pred p;\nsetp.ne.u32 p, %3, 0;\n@p st.relaxed.gpu.global.v2.u32 [%0], {%1,%2};\n}"
                 :: "l"(p), "r"(a), "r"(b), "r"((uint32_t)c) : "memory");
}

__device__ __forceinline__ void st_rlx128_if(bool c, uint32_t* p, uint32_t a, uint32_t b, uint32_t d, uint32_t e) {
    asm volatile("{\n.reg .pred p;\nsetp.ne.u32 p, %5, 0;\n@p st.relaxed.gpu.global.v4.u32 [%0], {%1,%2,%3,%4};\n}"
                 :: "l"(p), "r"(a), "r"(b), "r"(d), "r"(e), "r"((uint32_t)c) : "memory");
}
__device__ __forceinline__ float bf_lo(uint32_t w) { return __uint_as_float(w << 16); }
__device__ __forceinline__ float bf_hi(uint32_t w) { return __uint_as_float(w & 0xffff0000u); }
__device__ __forceinline__ uint32_t pack_bf(float lo, float hi) {
    __nv_bfloat162 v = __floats2bfloat162_rn(lo, hi);
    return *reinterpret_cast<uint32_t*>(&v);
}
__device__ __forceinline__ float rbf(float x) { return __uint_as_float(pack_bf(0.f, x)); }
__device__ __forceinline__ uint32_t enc(uint32_t w) { return w ? w : 0x80000000u; }

__device__ __forceinline__ float warp_sum(float v) {
#pragma unroll
    for (int o = 16; o > 0; o >>= 1) v += __shfl_xor_sync(0xffffffffu, v, o);
    return v;
}

__device__ __forceinline__ void layernorm_row(const uint4& r0, const uint4& r1, int lane, uint32_t dst_row) {
    const bool act = lane < 28;
    float v[16];
    const uint32_t w[8] = {r0.x, r0.y, r0.z, r0.w, r1.x, r1.y, r1.z, r1.w};
#pragma unroll
    for (int i = 0; i < 8; i++) { v[2 * i] = act ? bf_lo(w[i]) : 0.f; v[2 * i + 1] = act ? bf_hi(w[i]) : 0.f; }
    float s = 0.f;
#pragma unroll
    for (int i = 0; i < 16; i++) s += v[i];
    const float mean = warp_sum(s) / DM;
    float q = 0.f;
#pragma unroll
    for (int i = 0; i < 16; i++) { const float d = v[i] - mean; q = fmaf(d, d, q); }
    const float var = warp_sum(act ? q : 0.f) / DM;
    const float mb = rbf(mean);
    const float sd = rbf(sqrtf(rbf(rbf(var) + 1e-5f)));
    const float rs = 1.0f / sd;
    uint32_t o[8];
#pragma unroll
    for (int i = 0; i < 8; i++) o[i] = pack_bf(rbf(v[2 * i] - mb) * rs, rbf(v[2 * i + 1] - mb) * rs);
    if (act) {
        asm volatile("st.shared.v4.u32 [%0], {%1,%2,%3,%4};" :: "r"(dst_row + lane * 16), "r"(o[0]), "r"(o[1]), "r"(o[2]), "r"(o[3]) : "memory");
        asm volatile("st.shared.v4.u32 [%0], {%1,%2,%3,%4};" :: "r"(dst_row + 448 + lane * 16), "r"(o[4]), "r"(o[5]), "r"(o[6]), "r"(o[7]) : "memory");
    }
}

template <class T> __device__ __forceinline__ T* pin(T* p) { asm volatile("" : "+l"(p)); return p; }
__device__ __forceinline__ uint32_t pin(uint32_t v) { asm volatile("" : "+r"(v)); return v; }
__device__ __forceinline__ void sts64(uint32_t a, float x, float y) {
    asm volatile("st.shared.v2.f32 [%0], {%1,%2};" :: "r"(a), "f"(x), "f"(y) : "memory");
}
__device__ __forceinline__ void sts128(uint32_t a, float x, float y, float z, float w) {
    asm volatile("st.shared.v4.f32 [%0], {%1,%2,%3,%4};" :: "r"(a), "f"(x), "f"(y), "f"(z), "f"(w) : "memory");
}
__device__ __forceinline__ float2 lds64f(uint32_t a) {
    float2 v;
    asm volatile("ld.shared.v2.f32 {%0,%1}, [%2];" : "=f"(v.x), "=f"(v.y) : "r"(a) : "memory");
    return v;
}
__device__ __forceinline__ float4 lds128f(uint32_t a) {
    float4 v;
    asm volatile("ld.shared.v4.f32 {%0,%1,%2,%3}, [%4];" : "=f"(v.x), "=f"(v.y), "=f"(v.z), "=f"(v.w) : "r"(a) : "memory");
    return v;
}
__device__ __forceinline__ uint32_t add_bf2(uint32_t a, uint32_t b) {
    uint32_t d;
    asm("add.rn.bf16x2 %0, %1, %2;" : "=r"(d) : "r"(a), "r"(b));
    return d;
}
__device__ __forceinline__ uint32_t neg_sq_relu_bf2(uint32_t a) {
    uint32_t d;
    asm("{\n.reg .b32 r, n;\nmax.bf16x2 r, %1, %2;\nneg.bf16x2 n, r;\nmul.rn.bf16x2 %0, r, n;\n}" : "=r"(d) : "r"(a), "r"(0));
    return d;
}

#define V4(v) "+r"(v.x), "+r"(v.y), "+r"(v.z), "+r"(v.w)
#define POLL_HEAD(label) "mov.u32 it, 0;\n" label ":\nadd.u32 it, it, 1;\nsetp.lt.u32 c, it, 4194304;\n"
#define POLL_EXIT(label) "and.pred q, q, c;\nvote.sync.any.pred q, q, 0xffffffff;\n@!q bra " label "_END;\n"
#define POLL_LD(p, regs, addr) "@" p " ld.relaxed.gpu.global.v4.u32 {" regs "}, [" addr "];\n"
__device__ __forceinline__ void poll_nz(uint4& v, const uint32_t* p) {
    asm volatile("{\n.reg .pred p0, q, c;\n.reg .b32 t, it;\n" POLL_HEAD("PA")
                 "min.u32 t, %0, %1;\nmin.u32 t, t, %2;\nmin.u32 t, t, %3;\nsetp.eq.u32 p0, t, 0;\nmov.pred q, p0;\n"
                 POLL_EXIT("PA") POLL_LD("p0", "%0,%1,%2,%3", "%4") "bra PA;\nPA_END:\n}"
                 : V4(v) : "l"(p) : "memory");
}
__device__ __forceinline__ void poll_nz_until(uint4& v, const uint32_t* p, uint32_t bar) {
    asm volatile("{\n.reg .pred p0, q, c;\n.reg .b32 t, it;\n" POLL_HEAD("PF")
                 "min.u32 t, %0, %1;\nmin.u32 t, t, %2;\nmin.u32 t, t, %3;\nsetp.eq.u32 p0, t, 0;\nmov.pred q, p0;\n"
                 POLL_EXIT("PF") POLL_LD("p0", "%0,%1,%2,%3", "%4")
                 "mbarrier.test_wait.parity.shared.b64 q, [%5], 0;\nvote.sync.all.pred q, q, 0xffffffff;\n@!q bra PF;\nPF_END:\n}"
                 : V4(v) : "l"(p), "r"(bar) : "memory");
}
__device__ __forceinline__ void poll_nz2(uint4& v, uint4& w, const uint32_t* p) {
    asm volatile("{\n.reg .pred p0, p1, q, c;\n.reg .b32 t, u, it;\n" POLL_HEAD("PB")
                 "min.u32 t, %0, %1;\nmin.u32 t, t, %2;\nmin.u32 t, t, %3;\nsetp.eq.u32 p0, t, 0;\n"
                 "min.u32 u, %4, %5;\nmin.u32 u, u, %6;\nmin.u32 u, u, %7;\nsetp.eq.u32 p1, u, 0;\nor.pred q, p0, p1;\n"
                 POLL_EXIT("PB") POLL_LD("p0", "%0,%1,%2,%3", "%8") POLL_LD("p1", "%4,%5,%6,%7", "%8+512") "bra PB;\nPB_END:\n}"
                 : V4(v), V4(w) : "l"(p) : "memory");
}
__device__ __forceinline__ void poll_nz_pair(uint32_t& v, uint32_t& w, const uint32_t* p) {
    asm volatile("{\n.reg .pred q, c;\n.reg .b32 t, it;\n" POLL_HEAD("PC")
                 "ld.relaxed.gpu.global.u32 %0, [%2];\nld.relaxed.gpu.global.u32 %1, [%2+64];\n"
                 "min.u32 t, %0, %1;\nsetp.eq.u32 q, t, 0;\n"
                 POLL_EXIT("PC") "bra PC;\nPC_END:\n}"
                 : "=&r"(v), "=&r"(w) : "l"(p) : "memory");
}
__device__ __forceinline__ void poll_nz4(uint4& a, uint4& b, uint4& c, uint4& d, const uint32_t* p) {
    asm volatile("{\n.reg .pred p0, p1, p2, p3, q, c;\n.reg .b32 t, it;\n" POLL_HEAD("PD")
                 "min.u32 t, %0, %1;\nmin.u32 t, t, %2;\nmin.u32 t, t, %3;\nsetp.eq.u32 p0, t, 0;\n"
                 "min.u32 t, %4, %5;\nmin.u32 t, t, %6;\nmin.u32 t, t, %7;\nsetp.eq.u32 p1, t, 0;\n"
                 "min.u32 t, %8, %9;\nmin.u32 t, t, %10;\nmin.u32 t, t, %11;\nsetp.eq.u32 p2, t, 0;\n"
                 "min.u32 t, %12, %13;\nmin.u32 t, t, %14;\nmin.u32 t, t, %15;\nsetp.eq.u32 p3, t, 0;\n"
                 "or.pred q, p0, p1;\nor.pred q, q, p2;\nor.pred q, q, p3;\n"
                 POLL_EXIT("PD") POLL_LD("p0", "%0,%1,%2,%3", "%16") POLL_LD("p1", "%4,%5,%6,%7", "%16+512")
                 POLL_LD("p2", "%8,%9,%10,%11", "%16+1024") POLL_LD("p3", "%12,%13,%14,%15", "%16+1536") "bra PD;\nPD_END:\n}"
                 : V4(a), V4(b), V4(c), V4(d) : "l"(p) : "memory");
}
__device__ __forceinline__ void poll_sign4(uint4& a, uint4& b, uint4& c, uint4& d, const uint32_t* p) {
    asm volatile("{\n.reg .pred p0, p1, p2, p3, q, c;\n.reg .b32 t, it;\n" POLL_HEAD("PE")
                 "lop3.b32 t, %0, %1, %2, 0x80;\nlop3.b32 t, t, %3, 0x80000000, 0x2a;\nsetp.ne.u32 p0, t, 0;\n"
                 "lop3.b32 t, %4, %5, %6, 0x80;\nlop3.b32 t, t, %7, 0x80000000, 0x2a;\nsetp.ne.u32 p1, t, 0;\n"
                 "lop3.b32 t, %8, %9, %10, 0x80;\nlop3.b32 t, t, %11, 0x80000000, 0x2a;\nsetp.ne.u32 p2, t, 0;\n"
                 "lop3.b32 t, %12, %13, %14, 0x80;\nlop3.b32 t, t, %15, 0x80000000, 0x2a;\nsetp.ne.u32 p3, t, 0;\n"
                 "or.pred q, p0, p1;\nor.pred q, q, p2;\nor.pred q, q, p3;\n"
                 POLL_EXIT("PE") POLL_LD("p0", "%0,%1,%2,%3", "%16") POLL_LD("p1", "%4,%5,%6,%7", "%16+256")
                 POLL_LD("p2", "%8,%9,%10,%11", "%16+512") POLL_LD("p3", "%12,%13,%14,%15", "%16+768") "bra PE;\nPE_END:\n}"
                 : V4(a), V4(b), V4(c), V4(d) : "l"(p) : "memory");
}

constexpr uint32_t ONES = 0x3f803f80u;

__device__ __forceinline__ void ffn1_finish(uint32_t bar, uint32_t a_w1, uint32_t a_part, uint32_t a_stat,
                                            uint32_t bias_a, uint32_t bias_b, uint32_t* dst) {
    float w0[4] = {}, w1[4] = {}, w2[4] = {}, w3[4] = {};
    mbar_wait(bar, 0);
#pragma unroll 1
    for (int s = 0; s < 28; s += 14) {
        uint4 bw[14];
#pragma unroll
        for (int i = 0; i < 14; i++) bw[i] = ldm4t(a_w1 + (s + i) * 1024);
#pragma unroll
        for (int i = 0; i < 14; i += 2) {
            mma16816(w0, ONES, ONES, ONES, ONES, bw[i].x, bw[i].y);
            mma16816(w1, ONES, ONES, ONES, ONES, bw[i].z, bw[i].w);
            mma16816(w2, ONES, ONES, ONES, ONES, bw[i + 1].x, bw[i + 1].y);
            mma16816(w3, ONES, ONES, ONES, ONES, bw[i + 1].z, bw[i + 1].w);
        }
    }
    const float cs0 = w0[0] + w2[0], cs1 = w0[1] + w2[1], cs2 = w1[0] + w3[0], cs3 = w1[1] + w3[1];
    asm volatile("barrier.sync 2, 288;" ::: "memory");
    float2 sq[7];
    float4 p[7];
#pragma unroll
    for (int w = 0; w < 7; w++) sq[w] = lds64f(a_stat + w * 64);
#pragma unroll
    for (int w = 0; w < 7; w++) p[w] = lds128f(a_part + w * 1024);
    const float sum = ((sq[0].x + sq[1].x) + (sq[2].x + sq[3].x)) + ((sq[4].x + sq[5].x) + sq[6].x);
    const float mean = sum * (1.0f / DM);
    const float msq = (((sq[0].y + sq[1].y) + (sq[2].y + sq[3].y)) + ((sq[4].y + sq[5].y) + sq[6].y)) * (1.0f / DM);
    const float var = fmaxf(fmaf(-mean, mean, msq), 0.f);
    float sd, rs;
    asm("sqrt.approx.ftz.f32 %0, %1;" : "=f"(sd) : "f"(rbf(rbf(var) + 1e-5f)));
    asm("rcp.approx.ftz.f32 %0, %1;" : "=f"(rs) : "f"(rbf(sd)));
    const float mb = rbf(fmaf(fmaf(-mean, (float)DM, sum), 1.0f / DM, mean));
    const float s0 = fmaf(-mb, cs0, ((p[0].x + p[1].x) + (p[2].x + p[3].x)) + ((p[4].x + p[5].x) + p[6].x));
    const float s1 = fmaf(-mb, cs1, ((p[0].y + p[1].y) + (p[2].y + p[3].y)) + ((p[4].y + p[5].y) + p[6].y));
    const float s2 = fmaf(-mb, cs2, ((p[0].z + p[1].z) + (p[2].z + p[3].z)) + ((p[4].z + p[5].z) + p[6].z));
    const float s3 = fmaf(-mb, cs3, ((p[0].w + p[1].w) + (p[2].w + p[3].w)) + ((p[4].w + p[5].w) + p[6].w));
    st_rlx64(dst, neg_sq_relu_bf2(add_bf2(pack_bf(s0 * rs, s1 * rs), bias_a)),
             neg_sq_relu_bf2(add_bf2(pack_bf(s2 * rs, s3 * rs), bias_b)));
}

__global__ void __launch_bounds__(NTHREADS, 1)
fused_decode_kernel(Scratch* gs, const char* __restrict__ kc,
                    const __nv_bfloat16* __restrict__ x, const __nv_bfloat16* __restrict__ wq,
                    const __nv_bfloat16* __restrict__ b1, const __nv_bfloat16* __restrict__ b2,
                    __nv_bfloat16* __restrict__ out,
                    const __grid_constant__ CUtensorMap tm_k, const __grid_constant__ CUtensorMap tm_v,
                    const __grid_constant__ CUtensorMap tm_wo, const __grid_constant__ CUtensorMap tm_w1,
                    const __grid_constant__ CUtensorMap tm_w2) {
    if (threadIdx.x == 256)
        asm volatile("cp.async.bulk.prefetch.L2.global [%0], %1;"
                     :: "l"(kc + ((size_t)(((blockIdx.x & 7) * NH + (blockIdx.x >> 3)) * 2 + ((blockIdx.x >> 3) & 1)) << 20)),
                        "r"(STAGE) : "memory");
    extern __shared__ __align__(1024) uint8_t sp[];
    const uint32_t sb = pin(smem_u32(sp));

    const int tid = threadIdx.x, warp = tid >> 5, lane = tid & 31;
    const int g = lane >> 2, t4 = lane & 3;
    const int cta = blockIdx.x;
    const int hd = cta >> 3, bj = cta & 7;
    const bool tail = bj < 7;
    const int ri = (hd * 7 + bj) >> 1;
    const bool ffn2 = (hd + bj) & 1;
    const int bg = ri & 1, cg = ri >> 1;
    const uint32_t bar_full = sb + OFF_BAR, bar_empty = bar_full + NS * 8, bar_w = bar_empty + NS * 8;
    const uint32_t s_wq = sb + OFF_WO, s_est = sb + OFF_M + 64;

    uint32_t epoch;
    asm volatile("ld.relaxed.gpu.global.u32 %0, [%1];" : "=r"(epoch) : "l"(gs->epoch[cta]) : "memory");
    const int grp0 = (bj * NH + hd) * (SK / 8), flip = (hd & 1) * (KT / 2);
    uint64_t pol;
    asm volatile("createpolicy.fractional.L2::evict_first.b64 %0, 1.0;" : "=l"(pol));
    if (tid == 256) {
#pragma unroll
        for (int s = 0; s < D0; s++) mbar_init(bar_full + s * 8, 1);
        asm volatile("fence.mbarrier_init.release.cluster;" ::: "memory");
#pragma unroll
        for (int s = 0; s < D0; s++) {
            mbar_expect_tx(bar_full + s * 8, STAGE);
            tma_tile(sb + OFF_RING + s * STAGE, &tm_k, grp0 + (s ^ flip) * 4, bar_full + s * 8, pol);
        }
    }
    uint4 xr0 = make_uint4(0, 0, 0, 0), xr1 = xr0;
    if (warp < 8) {
        if (lane < 28) {
            xr0 = ldg128_now(x + warp * DM + lane * 8);
            xr1 = ldg128_now(x + warp * DM + 224 + lane * 8);
        }
        const int row = tid >> 2, ch = tid & 3;
        const uint32_t d = s_wq + row * 64 + ((ch ^ ((row >> 1) & 3)) << 4);
        const __nv_bfloat16* p = wq + (size_t)row * (NH * DH) + cta * 32 + ch * 8;
#pragma unroll
        for (int i = 0; i < 7; i++)
            asm volatile("cp.async.cg.shared.global.L2::128B [%0], [%1], 16;"
                         :: "r"(d + i * 4096), "l"(p + (size_t)i * 64 * (NH * DH)) : "memory");
    }

    if (warp == 8) {
        if (lane != 0) return;
#pragma unroll
        for (int s = D0; s < 2 * NS + 9; s++) mbar_init(bar_full + s * 8, (s >= NS && s < 2 * NS) || s == 2 * NS + 1 ? 8 : 1);
        asm volatile("fence.mbarrier_init.release.cluster;" ::: "memory");
        asm volatile("st.volatile.shared.v2.u32 [%0], {%1,%2};" :: "r"(s_est), "r"(0), "r"(clock32()) : "memory");
        asm volatile("barrier.arrive 3, 288;" ::: "memory");
        asm volatile("barrier.arrive 7, 64;" ::: "memory");
        uint32_t t = D0, landed = 0, pf = NS;
#pragma unroll 1
        for (int it = 0; t < NT && it < 16 * SPIN_MAX; it++) {
            if (landed < t && mbar_test(bar_full + (landed & (NS - 1)) * 8, (landed / NS) & 1)) {
                landed++;
                if (((landed + cta) & 3) == 0) asm volatile("red.relaxed.gpu.global.add.u32 [%0], 4;" :: "l"(gs->prog[~pin(epoch) & 1]) : "memory");
            }
            const uint32_t s = t & (NS - 1);
            if (t < NS) {
                if (t - landed >= D0) continue;
            } else {
                if (t == NS && pf - landed < D0 && !mbar_test(bar_empty, 0)) {
                    asm volatile("cp.async.bulk.prefetch.tensor.4d.L2.global [%0, {%1, %1, %1, %2}];"
                                 :: "l"(&tm_k), "r"(0), "r"(grp0 + (pf ^ flip) * 4) : "memory");
                    pf++;
                }
                if (t - landed >= NS) continue;
                if (t - landed >= 2) {
                    uint32_t v, c0;
                    asm volatile("ld.volatile.shared.v2.u32 {%0,%1}, [%2];" : "=r"(v), "=r"(c0) : "r"(s_est) : "memory");
                    if (t * NCTA > v + min(((clock32() - c0) * 7) >> 6, 256u) + (t - landed > 2 ? WIN : WIN + EXTRA)) continue;
                }
                if (!mbar_test(bar_empty + s * 8, (t / NS - 1) & 1)) continue;
            }
            mbar_expect_tx(bar_full + s * 8, STAGE);
            tma_tile(sb + OFF_RING + s * STAGE, t < KT ? &tm_k : &tm_v, grp0 + ((t ^ flip) & (KT - 1)) * 4, bar_full + s * 8, pol);
            t++;
        }
        asm volatile("red.relaxed.gpu.global.add.u32 [%0], %1;" :: "l"(gs->prog[~epoch & 1]), "r"(NT - ((landed + (cta & 3)) & ~3u)) : "memory");
        if (!tail) return;
        mbar_wait(bar_full + ((NT - 2) & (NS - 1)) * 8, ((NT - 2) / NS) & 1);
        for (const uint32_t c0 = clock32(); clock32() - c0 < WO_DELAY;) {}
        mbar_expect_tx(bar_w, DH * 128);
        tma_2d(sb + OFF_WO, &tm_wo, bj * 64, hd * DH, bar_w);
        if (!ffn2) {
            mbar_wait(bar_w, 0);
            mbar_expect_tx(bar_w + 16, DM * 64);
            tma_2d(sb + OFF_W, &tm_w1, ri * 32, 0, bar_w + 16);
            tma_2d(sb + OFF_W + 224 * 64, &tm_w1, ri * 32, 224, bar_w + 16);
        } else {
            mbar_wait(bar_w + 8, 0);
#pragma unroll
            for (int i = 0; i < 7; i++) {
                mbar_expect_tx(bar_w + (2 + i) * 8, 8192);
                tma_2d(sb + OFF_RING + i * 8192, &tm_w2, cg * 16, i * 256, bar_w + (2 + i) * 8);
            }
        }
        return;
    }

    const uint32_t par = (epoch + 1) & 1;
    if (warp == 10) {
        __nanosleep(CLEAR_NS);
        const uint4 z = make_uint4(0, 0, 0, 0);
        for (int i = lane; i < MAIL_VECS; i += 32) reinterpret_cast<uint4*>(&gs->mail)[cta * MAIL_VECS + i] = z;
        reinterpret_cast<uint4*>(gs->q[par ^ 1])[cta * 32 + lane] = z;
        if (cta == 0 && lane == 0) { gs->prog[par ^ 1][0] = 0; gs->cleared[par ^ 1][0] = 0; }
        __syncwarp();
        if (lane == 0) {
            asm volatile("red.release.gpu.global.add.u32 [%0], 1;" :: "l"(gs->cleared[par]) : "memory");
            uint32_t n = 0;
#pragma unroll 1
            for (int it = 0; n < NCTA && it < SPIN_MAX; it++) {
                __nanosleep(1000);
                asm volatile("ld.acquire.gpu.global.u32 %0, [%1];" : "=r"(n) : "l"(gs->cleared[par]) : "memory");
            }
        }
        __syncwarp();
        asm volatile("barrier.arrive 8, 288;" ::: "memory");
        return;
    }
    const uint32_t a_w1 = pin(sb + OFF_W + (((lane >> 3) & 1) * 8 + (lane & 7)) * 64 + (((lane >> 4) ^ ((lane >> 1) & 3)) << 4));
    const uint32_t a_stat = pin(sb + OFF_D + 7168 + g * 8);

    if (warp == 9) {
        uint32_t bias_a = 0, bias_b = 0;
        if (tail && !ffn2) {
            bias_a = ldg32_now(b1 + ri * 32 + 16 + t4 * 2);
            bias_b = ldg32_now(b1 + ri * 32 + 24 + t4 * 2);
        }
        uint4 q = make_uint4(0, 0, 0, 0);
        poll_nz(q, &gs->q[par][bj * (NH * DH / 2) + hd * (DH / 2) + lane * 4]);
        *reinterpret_cast<uint4*>(sp + OFF_Q + lane * 16) = q;
        asm volatile("barrier.arrive 5, 288;" ::: "memory");
        asm volatile("barrier.sync 7, 64;" ::: "memory");
        if (lane == 0) {
            asm volatile("prefetch.tensormap [%0];" :: "l"(&tm_v) : "memory");
            asm volatile("prefetch.tensormap [%0];" :: "l"(&tm_wo) : "memory");
            asm volatile("prefetch.tensormap [%0];" :: "l"(ffn2 ? &tm_w2 : &tm_w1) : "memory");
            uint32_t v = 0;
#pragma unroll 1
            for (int it = 0; v + WIN < (NT - 1) * NCTA && it < SPIN_MAX; it++) {
                asm volatile("ld.relaxed.gpu.global.u32 %0, [%1];" : "=r"(v) : "l"(gs->prog[par]) : "memory");
                asm volatile("st.volatile.shared.v2.u32 [%0], {%1,%2};" :: "r"(s_est), "r"(v), "r"(clock32()) : "memory");
                __nanosleep(HSLEEP);
            }
        }
        __syncwarp();
        if (tail && !ffn2) {
            ffn1_finish(bar_w + 16, a_w1 ^ 32, pin(sb + OFF_D + 512 + lane * 16), a_stat, bias_a, bias_b,
                        pin(&gs->mail.g[((g >> 2) * NMSG + ri * 2 + 1) * 32 + (g & 3) * 8 + (t4 ^ 1) * 2]));
        }
        return;
    }

    asm volatile("cp.async.commit_group;" ::: "memory");
    uint32_t c0w = 0, c1w = 0;
    if (!tail) {
        if (warp < 7) {
            const __nv_bfloat16* p = x + (hd >> 1) * DM + warp * 64 + (hd & 1) * 32 + ((lane >> 2) & 1) * 16 + t4 * 2;
            c0w = ldg32_now(p);
            c1w = ldg32_now(p + 8);
        }
    } else if (warp == 7) {
        if (ffn2) {
            c0w = ldg32_now(b2 + cg * 16 + (lane & 1) * 8 + (g & 6));
            c0w = __byte_perm(c0w, 0, (g & 1) ? 0x3232 : 0x1010);
        } else {
            c0w = ldg32_now(b1 + ri * 32 + t4 * 2);
            c1w = ldg32_now(b1 + ri * 32 + 8 + t4 * 2);
        }
    }

    layernorm_row(xr0, xr1, lane, sb + OFF_C + warp * (XP * 2));
    asm volatile("cp.async.wait_group 0;" ::: "memory");
    asm volatile("barrier.sync 3, 288;" ::: "memory");

    float* red_b = reinterpret_cast<float*>(sp + OFF_B);
    if (warp < 7) {
        float acc[4][4] = {};
#pragma unroll
        for (int p = 0; p < 2; p++) {
            const uint4 a = ldm4(sb + OFF_C + (lane & 7) * (XP * 2) + (warp * 64 + p * 32 + (lane >> 3) * 8) * 2);
#pragma unroll
            for (int s = 0; s < 2; s++) {
                const int row = warp * 64 + p * 32 + s * 16 + ((lane >> 3) & 1) * 8 + (lane & 7);
#pragma unroll
                for (int np = 0; np < 2; np++) {
                    const int ch = np * 2 + (lane >> 4);
                    const uint4 bw = ldm4t(s_wq + row * 64 + ((ch ^ ((row >> 1) & 3)) << 4));
                    mma16816(acc[np * 2], s ? a.z : a.x, 0, s ? a.w : a.y, 0, bw.x, bw.y);
                    mma16816(acc[np * 2 + 1], s ? a.z : a.x, 0, s ? a.w : a.y, 0, bw.z, bw.w);
                }
            }
        }
#pragma unroll
        for (int n = 0; n < 4; n++)
            *reinterpret_cast<float2*>(red_b + (warp * 8 + g) * 40 + n * 8 + t4 * 2) = make_float2(acc[n][0], acc[n][1]);
    }
    asm volatile("fence.proxy.async.shared::cta;" ::: "memory");
    cbar();
    if (tid < 128) {
        const int b = tid >> 4, wd = tid & 15;
        float s0 = 0.f, s1 = 0.f;
#pragma unroll
        for (int w = 0; w < 7; w++) {
            const float2 p = *reinterpret_cast<const float2*>(red_b + (w * 8 + b) * 40 + wd * 2);
            s0 += p.x; s1 += p.y;
        }
        st_rlx32(&gs->q[par][b * (NH * DH / 2) + cta * 16 + (wd & 3) * 4 + ((wd >> 2) & 1) * 2 + (wd >> 3)], enc(pack_bf(s0, s1)));
    }

    uint32_t* const p_o_st = pin(&gs->mail.o[(hd * 8 + warp) * 128 + bj * 16 + t4 * 4]);
    const uint32_t* const p_o_ld = pin(&gs->mail.o[(hd * 8 + warp) * 128 + lane * 4]);
    uint32_t* const p_p2_st = pin(gs->mail.p2 + ((bj * 16 + warp * 2 + (lane >> 4)) * 16 + hd) * 32 + (lane & 15) * 2);
    const uint32_t* p_in;
    uint32_t* p_res;
    if (!tail) {
        p_in = gs->mail.p2 + ((warp * 16 + hd) * 16 + (lane >> 3)) * 32 + (lane & 7) * 4;
        p_res = &gs->mail.h[(lane >> 3) % HREP][(warp * 2 + (hd & 1)) * 128 + (hd >> 1) * 16 + t4 * 4 + ((lane >> 2) & 1) * 2];
    } else if (!ffn2) {
        p_in = &gs->mail.h[ri % HREP][warp * 256 + lane * 4];
        p_res = &gs->mail.g[((g >> 2) * NMSG + ri * 2) * 32 + (g & 3) * 8 + t4 * 2];
    } else {
        const int b = bg * 4 + (lane & 2);
        p_in = warp < 7 ? &gs->mail.g[(bg * NMSG + warp * 16 + (g >> 2) * 8 + (t4 >> 1)) * 32 + (g & 3) * 8 + (t4 & 1) * 4]
                        : &gs->mail.h[ri % HREP][(cg >> 1) * 128 + b * 16 + (g >> 1) * 4 + (cg & 1) * 2 + (lane & 1)];
        p_res = reinterpret_cast<uint32_t*>(out + b * DM + cg * 16 + (lane & 1) * 8 + g);
    }
    p_in = pin(p_in);
    p_res = pin(p_res);
    const uint32_t a_wo = pin(sb + OFF_WO + (warp * 32 + (lane >> 4) * 8 + (lane & 7)) * 128 + ((((lane >> 3) & 1) ^ (lane & 7)) << 4));
    const uint32_t a_r2w = pin(sb + OFF_B + warp * 2048 + (t4 * 8 + ((g + 2 * t4) & 7)) * 16);
    const uint32_t a_r2r = pin(sb + OFF_B + (lane >> 3) * 512 +
                               ((warp >> 1) * 8 + ((lane + (warp & 6)) & 7)) * 16 + ((warp ^ (lane >> 3)) & 1) * 8);
    __nv_bfloat16* sc = reinterpret_cast<__nv_bfloat16*>(sp + OFF_A);

    float mx = -INFINITY;
    {
        uint4 q[8];
        asm volatile("barrier.sync 5, 288;" ::: "memory");
#pragma unroll
        for (int i = 0; i < 8; i++) q[i] = lds128(sb + OFF_Q + i * 64 + t4 * 16);
        const uint32_t ka = pin(sb + OFF_RING + (warp & 3) * 4096 + (lane & 7) * 128 + (((lane >> 3) ^ (lane & 7)) << 4));
        uint32_t* scw = reinterpret_cast<uint32_t*>(sc) + t4 * 4 + (warp & 1) * 2 + ((warp >> 1) & 1);
#pragma unroll 1
        for (int t = warp >> 2; t < KT; t += 2) {
            const int st = t & (NS - 1);
            mbar_wait(bar_full + st * 8, (t / NS) & 1);
            uint4 kf[8];
#pragma unroll
            for (int i = 0; i < 8; i++) kf[i] = ldm4((ka ^ ((i & 1) << 6)) + st * STAGE + (i >> 1) * 1024);
            float c[4][4] = {};
#pragma unroll
            for (int i = 0; i < 8; i++) {
                mma16816(c[(i & 1) * 2], q[i].x, q[i].y, q[i].z, q[i].w, kf[i].x, kf[i].y);
                mma16816(c[(i & 1) * 2 + 1], q[i].x, q[i].y, q[i].z, q[i].w, kf[i].z, kf[i].w);
            }
            __syncwarp();
            if (lane == 0) mbar_arrive2(bar_empty + st * 8);
            const uint32_t d = pack_bf((c[0][0] + c[2][0]) + (c[1][2] + c[3][2]), (c[0][1] + c[2][1]) + (c[1][3] + c[3][3]));
            const uint32_t sw = pack_bf(bf_lo(d) * 0.0625f, bf_hi(d) * 0.0625f);
            mx = fmaxf(mx, fmaxf(bf_lo(sw), bf_hi(sw)));
            if (lane < 4) scw[t * 16] = sw;
        }
    }

    {
        float* sm_m = reinterpret_cast<float*>(sp + OFF_M);
        mx = fmaxf(mx, __shfl_xor_sync(0xffffffffu, mx, 1));
        mx = fmaxf(mx, __shfl_xor_sync(0xffffffffu, mx, 2));
        if (lane == 0) sm_m[warp] = mx;
        cbar();
#pragma unroll
        for (int w = 0; w < 8; w++) mx = fmaxf(mx, sm_m[w]);
        float e[16], sum = 0.f;
#pragma unroll
        for (int i = 0; i < 4; i++) {
            const uint2 s = *reinterpret_cast<const uint2*>(sc + i * 1024 + tid * 4);
            e[i * 4 + 0] = expf(bf_lo(s.x) - mx); e[i * 4 + 1] = expf(bf_hi(s.x) - mx);
            e[i * 4 + 2] = expf(bf_lo(s.y) - mx); e[i * 4 + 3] = expf(bf_hi(s.y) - mx);
            sum += (e[i * 4] + e[i * 4 + 1]) + (e[i * 4 + 2] + e[i * 4 + 3]);
        }
        sum = warp_sum(sum);
        if (lane == 0) sm_m[8 + warp] = sum;
        cbar();
        sum = 0.f;
#pragma unroll
        for (int w = 0; w < 8; w++) sum += sm_m[8 + w];
        const float inv = 1.0f / sum;
#pragma unroll
        for (int i = 0; i < 4; i++)
            *reinterpret_cast<uint2*>(sc + i * 1024 + tid * 4) =
                make_uint2(pack_bf(e[i * 4] * inv, e[i * 4 + 1] * inv), pack_bf(e[i * 4 + 2] * inv, e[i * 4 + 3] * inv));
        asm volatile("barrier.sync 8, 288;" ::: "memory");
    }
    if (tid == 0) st_rlx32(gs->epoch[cta], epoch + 1);

    {
        float oa[4][4] = {}, ob[4][4] = {};
        const uint32_t va = pin(sb + OFF_RING + ((lane >> 3) & 1) * 4096 + (warp >> 1) * 1024 + (lane & 7) * 128 +
                                ((((warp & 1) * 4 + (lane >> 4)) ^ (lane & 7)) << 4));
        auto pv_tile = [&](int t, bool release) {
            const int st = t & (NS - 1);
            const uint4 p = lds128(sb + OFF_A + t * 64 + t4 * 16);
            const uint32_t va0 = pin(va + st * STAGE), va1 = pin(va0 ^ 32);
            mbar_wait(bar_full + st * 8, ((KT + t) / NS) & 1);
            const uint4 v0 = ldm4t(va0), v1 = ldm4t(va1), v2 = ldm4t(va0 + 8192), v3 = ldm4t(va1 + 8192);
            mma16816(oa[0], p.x, p.y, p.z, p.w, v0.x, v0.y);
            mma16816(oa[1], p.x, p.y, p.z, p.w, v0.z, v0.w);
            mma16816(oa[2], p.x, p.y, p.z, p.w, v1.x, v1.y);
            mma16816(oa[3], p.x, p.y, p.z, p.w, v1.z, v1.w);
            mma16816(ob[0], p.x, p.y, p.z, p.w, v2.x, v2.y);
            mma16816(ob[1], p.x, p.y, p.z, p.w, v2.z, v2.w);
            mma16816(ob[2], p.x, p.y, p.z, p.w, v3.x, v3.y);
            mma16816(ob[3], p.x, p.y, p.z, p.w, v3.z, v3.w);
            if (release) {
                __syncwarp();
                if (lane == 0) mbar_arrive(bar_empty + st * 8);
            }
        };
#pragma unroll 1
        for (int t = 0; t < KT - 4; t++) pv_tile(t, true);
#pragma unroll
        for (int t = KT - 4; t < KT; t++) pv_tile(t, false);
        st_rlx128_if(lane < 4, p_o_st,
                     enc(pack_bf(oa[0][0] + ob[0][2], oa[0][1] + ob[0][3])), enc(pack_bf(oa[1][0] + ob[1][2], oa[1][1] + ob[1][3])),
                     enc(pack_bf(oa[2][0] + ob[2][2], oa[2][1] + ob[2][3])), enc(pack_bf(oa[3][0] + ob[3][2], oa[3][1] + ob[3][3])));
    }

    if (!tail) {
        if (warp < 7) {
            uint4 v0 = make_uint4(0, 0, 0, 0), v1 = v0, v2 = v0, v3 = v0;
            poll_nz4(v0, v1, v2, v3, p_in);
            float a0 = (__uint_as_float(v0.x) + __uint_as_float(v1.x)) + (__uint_as_float(v2.x) + __uint_as_float(v3.x));
            float a1 = (__uint_as_float(v0.y) + __uint_as_float(v1.y)) + (__uint_as_float(v2.y) + __uint_as_float(v3.y));
            float a2 = (__uint_as_float(v0.z) + __uint_as_float(v1.z)) + (__uint_as_float(v2.z) + __uint_as_float(v3.z));
            float a3 = (__uint_as_float(v0.w) + __uint_as_float(v1.w)) + (__uint_as_float(v2.w) + __uint_as_float(v3.w));
#pragma unroll
            for (int o = 8; o <= 16; o <<= 1) {
                a0 += __shfl_xor_sync(0xffffffffu, a0, o);
                a1 += __shfl_xor_sync(0xffffffffu, a1, o);
                a2 += __shfl_xor_sync(0xffffffffu, a2, o);
                a3 += __shfl_xor_sync(0xffffffffu, a3, o);
            }
            st_rlx64_if(lane < 8 * HREP, p_res, enc(add_bf2(c0w, pack_bf(a0, a2))), enc(add_bf2(c1w, pack_bf(a1, a3))));
        }
        return;
    }

    {
        uint4 v = make_uint4(0, 0, 0, 0);
        for (const uint32_t c0 = clock32(); __all_sync(0xffffffffu, clock32() - c0 < O_HOLD && !mbar_test(bar_w, 0));) {}
        poll_nz_until(v, p_o_ld, bar_w);
        mbar_wait(bar_w, 0);
        uint4 a[2][4];
#pragma unroll
        for (int s = 0; s < 2; s++)
#pragma unroll
            for (int mt = 0; mt < 4; mt++) a[s][mt] = ldm4t((a_wo ^ (mt << 5)) + s * 2048);
        poll_nz(v, p_o_ld);
        float acc[4][4] = {};
#pragma unroll
        for (int mt = 0; mt < 4; mt++) mma16816(acc[mt], a[0][mt].x, a[0][mt].y, a[0][mt].z, a[0][mt].w, v.x, v.y);
#pragma unroll
        for (int mt = 0; mt < 4; mt++) mma16816(acc[mt], a[1][mt].x, a[1][mt].y, a[1][mt].z, a[1][mt].w, v.z, v.w);
#pragma unroll
        for (int mt = 0; mt < 4; mt += 2) {
            sts128(a_r2w + mt * 512, acc[mt][0], acc[mt][2], acc[mt][1], acc[mt][3]);
            sts128(a_r2w + mt * 512 + 512, acc[mt + 1][1], acc[mt + 1][3], acc[mt + 1][0], acc[mt + 1][2]);
        }
        cbar();
        float2 p[8];
#pragma unroll
        for (int w = 0; w < 8; w++) p[w] = lds64f(a_r2r + w * 2048);
        const float s0 = ((p[0].x + p[1].x) + (p[2].x + p[3].x)) + ((p[4].x + p[5].x) + (p[6].x + p[7].x));
        const float s1 = ((p[0].y + p[1].y) + (p[2].y + p[3].y)) + ((p[4].y + p[5].y) + (p[6].y + p[7].y));
        st_rlx64(p_p2_st, enc(__float_as_uint(s0)), enc(__float_as_uint(s1)));
        if (lane == 0) asm volatile("mbarrier.arrive.relaxed.cta.shared.b64 _, [%0];" :: "r"(bar_w + 8) : "memory");
    }

    if (!ffn2) {
        if (warp < 7) {
            const uint32_t c0 = clock32();
            uint4 v0 = make_uint4(0, 0, 0, 0), v1 = v0;
            const uint32_t a_part = pin(sb + OFF_D + warp * 1024 + lane * 16);
            mbar_wait(bar_w + 16, 0);
            uint4 bw[4][2];
#pragma unroll
            for (int s = 0; s < 4; s++) {
                bw[s][0] = ldm4t(a_w1 + warp * 4096 + s * 1024);
                bw[s][1] = ldm4t((a_w1 ^ 32) + warp * 4096 + s * 1024);
            }
            while (clock32() - c0 < H_HOLD) {}
            poll_nz2(v0, v1, p_in);
            const uint32_t hw[8] = {v0.x, v0.y, v0.z, v0.w, v1.x, v1.y, v1.z, v1.w};
            float c[4][4] = {}, cs[4] = {};
#pragma unroll
            for (int s = 0; s < 4; s++) {
                mma16816(cs, hw[2 * s], ONES, hw[2 * s + 1], ONES, hw[2 * s], hw[2 * s + 1]);
                mma16816(c[0], hw[2 * s], ONES, hw[2 * s + 1], ONES, bw[s][0].x, bw[s][0].y);
                mma16816(c[1], hw[2 * s], ONES, hw[2 * s + 1], ONES, bw[s][0].z, bw[s][0].w);
                mma16816(c[2], hw[2 * s], ONES, hw[2 * s + 1], ONES, bw[s][1].x, bw[s][1].y);
                mma16816(c[3], hw[2 * s], ONES, hw[2 * s + 1], ONES, bw[s][1].z, bw[s][1].w);
            }
            if (t4 == (g >> 1)) sts64(a_stat + warp * 64, (g & 1) ? cs[3] : cs[2], (g & 1) ? cs[1] : cs[0]);
            sts128(a_part, c[0][0], c[0][1], c[1][0], c[1][1]);
            sts128(a_part + 512, c[2][0], c[2][1], c[3][0], c[3][1]);
            asm volatile("barrier.arrive 2, 288;" ::: "memory");
        } else {
            ffn1_finish(bar_w + 16, a_w1, pin(sb + OFF_D + lane * 16), a_stat, c0w, c1w, p_res);
        }
    } else if (warp < 7) {
        const uint32_t a0 = pin(sb + OFF_RING + warp * 8192 +
                                (((lane >> 2) & 1) * 18 + (lane >> 4) * 8 + ((lane >> 1) & 1) * 4 + (lane & 1)) * 32 +
                                ((((lane >> 3) ^ (lane >> 1)) & 1) << 4));
        const uint32_t a_r5 = pin(sb + OFF_D + warp * 256 + (t4 >> 1) * 1856 + (g * 2 + (t4 & 1)) * 16);
        mbar_wait(bar_w + (2 + warp) * 8, 0);
        uint4 aw[2][8];
#pragma unroll
        for (int hh = 0; hh < 2; hh++)
#pragma unroll
            for (int s = 0; s < 8; s++) aw[hh][s] = ldm4t((a0 ^ ((s & 1) << 6)) + hh * 4096 + (s >> 1) * 1024);
        asm volatile("barrier.sync 6, 256;" ::: "memory");
        uint4 u[4];
#pragma unroll
        for (int i = 0; i < 4; i++) u[i] = ld_rlx128(p_in + i * 64);
        poll_sign4(u[0], u[1], u[2], u[3], p_in);
        float y[2][2][4] = {};
#pragma unroll
        for (int i = 0; i < 4; i++)
#pragma unroll
            for (int hh = 0; hh < 2; hh++) {
                mma16816(y[hh][0], aw[hh][2 * i].x, aw[hh][2 * i].y, aw[hh][2 * i].z, aw[hh][2 * i].w, u[i].x, u[i].y);
                mma16816(y[hh][1], aw[hh][2 * i + 1].x, aw[hh][2 * i + 1].y, aw[hh][2 * i + 1].z, aw[hh][2 * i + 1].w, u[i].z, u[i].w);
            }
        const bool lo = t4 < 2;
        sts128(a_r5, lo ? y[0][0][0] + y[0][1][0] : y[1][0][0] + y[1][1][0], lo ? y[0][0][1] + y[0][1][1] : y[1][0][1] + y[1][1][1],
               lo ? y[0][0][2] + y[0][1][2] : y[1][0][2] + y[1][1][2], lo ? y[0][0][3] + y[0][1][3] : y[1][0][3] + y[1][1][3]);
        asm volatile("barrier.arrive 4, 256;" ::: "memory");
    } else {
        uint32_t h0, h1;
        for (const uint32_t c0 = clock32(); clock32() - c0 < H_HOLD;) {}
        poll_nz_pair(h0, h1, p_in);
        asm volatile("barrier.arrive 6, 256;" ::: "memory");
        const uint32_t hres = __byte_perm(h0, h1, (g & 1) ? 0x7632 : 0x5410);
        const uint32_t a_r5 = pin(sb + OFF_D + lane * 8);
        asm volatile("barrier.sync 4, 256;" ::: "memory");
        float2 y[14];
#pragma unroll
        for (int w = 0; w < 14; w++) y[w] = lds64f(a_r5 + w * 256 + (w >= 7 ? 64 : 0));
        const float y0 = (((y[0].x + y[1].x) + (y[2].x + y[3].x)) + ((y[4].x + y[5].x) + (y[6].x + y[7].x))) +
                         (((y[8].x + y[9].x) + (y[10].x + y[11].x)) + (y[12].x + y[13].x));
        const float y1 = (((y[0].y + y[1].y) + (y[2].y + y[3].y)) + ((y[4].y + y[5].y) + (y[6].y + y[7].y))) +
                         (((y[8].y + y[9].y) + (y[10].y + y[11].y)) + (y[12].y + y[13].y));
        const uint32_t res = add_bf2(hres, add_bf2(pack_bf(-y0, -y1), c0w));
        asm volatile("st.global.u16 [%0], %1;" :: "l"(p_res), "h"((uint16_t)res) : "memory");
        asm volatile("st.global.u16 [%0+%2], %1;" :: "l"(p_res), "h"((uint16_t)(res >> 16)), "n"(DM * 2) : "memory");
    }
}

typedef CUresult (*EncodeTiledFn)(CUtensorMap*, CUtensorMapDataType, cuuint32_t, void*, const cuuint64_t*,
                                  const cuuint64_t*, const cuuint32_t*, const cuuint32_t*, CUtensorMapInterleave,
                                  CUtensorMapSwizzle, CUtensorMapL2promotion, CUtensorMapFloatOOBfill);

void encode_2d(EncodeTiledFn fn, CUtensorMap* tm, void* base, int rows, int cols, int box_rows, int box_cols,
               CUtensorMapSwizzle sw) {
    cuuint64_t dims[2] = {(cuuint64_t)cols, (cuuint64_t)rows};
    cuuint64_t strides[1] = {(cuuint64_t)cols * 2};
    cuuint32_t box[2] = {(cuuint32_t)box_cols, (cuuint32_t)box_rows};
    cuuint32_t es[2] = {1, 1};
    fn(tm, CU_TENSOR_MAP_DATA_TYPE_BFLOAT16, 2, base, dims, strides, box, es, CU_TENSOR_MAP_INTERLEAVE_NONE, sw,
       CU_TENSOR_MAP_L2_PROMOTION_L2_128B, CU_TENSOR_MAP_FLOAT_OOB_FILL_NONE);
}

void encode_kv(EncodeTiledFn fn, CUtensorMap* tm, void* base) {
    cuuint64_t dims[4] = {64, 8, 4, (cuuint64_t)NB * NH * SK / 8};
    cuuint64_t strides[3] = {DH * 2, 128, 8 * DH * 2};
    cuuint32_t box[4] = {64, 8, 4, TILE_KEYS / 8};
    cuuint32_t es[4] = {1, 1, 1, 1};
    fn(tm, CU_TENSOR_MAP_DATA_TYPE_BFLOAT16, 4, base, dims, strides, box, es, CU_TENSOR_MAP_INTERLEAVE_NONE,
       CU_TENSOR_MAP_SWIZZLE_128B, CU_TENSOR_MAP_L2_PROMOTION_NONE, CU_TENSOR_MAP_FLOAT_OOB_FILL_NONE);
}

}

extern "C" void kernel_launch(void* const* d_in, const int* in_sizes, int n_in, void* d_out, int out_size) {
    (void)in_sizes; (void)n_in; (void)out_size;
    static EncodeTiledFn encode = nullptr;
    static void* scratch = nullptr;
    if (!encode) {
        void* fn = nullptr;
        cudaDriverEntryPointQueryResult qr;
        cudaGetDriverEntryPoint("cuTensorMapEncodeTiled", &fn, cudaEnableDefault, &qr);
        encode = (EncodeTiledFn)fn;
        cudaGetSymbolAddress(&scratch, g_scratch);
        cudaFuncSetAttribute(fused_decode_kernel, cudaFuncAttributeMaxDynamicSharedMemorySize, SMEM_BYTES);
    }
    CUtensorMap tm_k, tm_v, tm_wo, tm_w1, tm_w2;
    encode_kv(encode, &tm_k, d_in[1]);
    encode_kv(encode, &tm_v, d_in[2]);
    encode_2d(encode, &tm_wo, d_in[4], NH * DH, DM, 256, 64, CU_TENSOR_MAP_SWIZZLE_128B);
    encode_2d(encode, &tm_w1, d_in[6], DM, FF, 224, 32, CU_TENSOR_MAP_SWIZZLE_64B);
    encode_2d(encode, &tm_w2, d_in[8], FF, DM, 256, 16, CU_TENSOR_MAP_SWIZZLE_32B);
    fused_decode_kernel<<<NCTA, NTHREADS, SMEM_BYTES, cudaStreamPerThread>>>(
        (Scratch*)scratch, (const char*)d_in[1], (const __nv_bfloat16*)d_in[0], (const __nv_bfloat16*)d_in[3], (const __nv_bfloat16*)d_in[7],
        (const __nv_bfloat16*)d_in[9], (__nv_bfloat16*)d_out, tm_k, tm_v, tm_wo, tm_w1, tm_w2);
}
```
